```python
import torch

def _softmax(x, axis=-1):
    return torch.softmax(x, dim=axis)

def _gelu(x):
    return torch.nn.functional.gelu(x, approximate='tanh')

def _silu(x):
    return torch.nn.functional.silu(x)

def _sigmoid(x):
    return torch.sigmoid(x)

def _layernorm(x, axis=-1, eps=1e-05):
    m = x.mean(dim=axis, keepdim=True)
    v = x.var(dim=axis, keepdim=True, unbiased=False)
    return (x - m) / torch.sqrt(v + eps)

def _scatter_add(tgt, idx, src, axis=0):
    return tgt.clone().index_add_(axis, idx, src)

def _segment_sum(src, seg, n):
    out = torch.zeros((n,) + src.shape[1:], dtype=src.dtype)
    return out.index_add_(0, seg, src)

def _pad(x, pw):
    flat = tuple((v for pair in reversed(pw) for v in pair))
    return torch.nn.functional.pad(x, flat)
kernel_name = 'adaLN_cond__sliding_local_dilated__swiglu_ffn__prompt'

def setup_inputs():

    _w = lambda a: (lambda t: t.to(torch.bfloat16) if t.is_floating_point() else t)(torch.as_tensor(a))

    def _A_setup():
        B, S, D = (1, 2048, 1024)
        return {'x': _w((lambda *s: torch.randn(*s, dtype=torch.bfloat16) * 0.05)(B, S, D)), 'wqkv': _w((lambda *s: torch.randn(*s, dtype=torch.bfloat16) * 0.05)(D, 3 * D)), 'wo': _w((lambda *s: torch.randn(*s, dtype=torch.bfloat16) * 0.05)(D, D))}
    _A_in = _A_setup()

    def _B_setup():
        B, S, D, F = (1, 2048, 1024, 3584)
        return {'x': _w((lambda *s: torch.randn(*s, dtype=torch.bfloat16) * 0.05)(B, S, D)), 'w_gate': _w((lambda *s: torch.randn(*s, dtype=torch.bfloat16) * 0.05)(D, F)), 'w_up': _w((lambda *s: torch.randn(*s, dtype=torch.bfloat16) * 0.05)(D, F)), 'w_down': _w((lambda *s: torch.randn(*s, dtype=torch.bfloat16) * 0.05)(F, D))}
    _B_in = _B_setup()
    return {'A_x': _A_in['x'], 'A_wqkv': _A_in['wqkv'], 'A_wo': _A_in['wo'], 'B_x': _B_in['x'], 'B_w_gate': _B_in['w_gate'], 'B_w_up': _B_in['w_up'], 'B_w_down': _B_in['w_down'], 'c': _w((lambda *s: torch.randn(*s, dtype=torch.bfloat16) * 0.1)(1, 1024) * 8.0), 'w_mod': _w((lambda *s: torch.randn(*s, dtype=torch.bfloat16) * 0.1)(1024, 6 * 1024) * 1024 ** (-0.5) * 8.0)}

def reference(A_x, A_wqkv, A_wo, B_x, B_w_gate, B_w_up, B_w_down, c, w_mod):

    def _A_ref(x, wqkv, wo):
        B, S, D = x.shape
        H = 32
        Dh = D // H
        W, dil = (8, 2)
        qkv = (lambda x, *d: x.permute(*d))((x @ wqkv).reshape(B, S, 3, H, Dh), 2, 0, 3, 1, 4)
        q, k, v = (qkv[0], qkv[1], qkv[2])
        scale = Dh ** (-0.5)
        pos = torch.arange(S)
        off = torch.arange(W) * dil
        idx = pos[:, None] - off[None, :]
        mask = idx >= 0
        idx_c = torch.where(mask, idx, 0).reshape(-1)
        kg = k[:, :, idx_c, :].reshape(B, H, S, W, Dh)
        vg = v[:, :, idx_c, :].reshape(B, H, S, W, Dh)
        logits = torch.einsum('bhsd,bhswd->bhsw', q, kg) * scale
        logits = torch.where(mask[None, None, :, :], logits, -1000000000.0)
        attn = _softmax(logits, axis=-1)
        o = torch.einsum('bhsw,bhswd->bhsd', attn, vg)
        return (lambda x, *d: x.permute(*d))(o, 0, 2, 1, 3).reshape(B, S, D) @ wo

    def _B_ref(x, w_gate, w_up, w_down):
        g = _silu(x @ w_gate)
        u = x @ w_up
        return g * u @ w_down
    x = A_x
    mod = (_silu(c) @ w_mod).reshape(c.shape[0], 6, 1, -1)
    sa, ca, ga, sb, cb, gb = (mod[:, 0].clone(), mod[:, 1].clone(), mod[:, 2].clone(), mod[:, 3].clone(), mod[:, 4].clone(), mod[:, 5].clone())
    h = _layernorm(x, axis=-1) * (1 + ca) + sa
    x = x + ga * _A_ref(h, A_wqkv, A_wo)
    h = _layernorm(x, axis=-1) * (1 + cb) + sb
    x = x + gb * _B_ref(h, B_w_gate, B_w_up, B_w_down)
    return x
```

```cpp
#include <cuda_runtime.h>
#include <cuda.h>
#include <cuda_bf16.h>
#include <stdint.h>
#include <stddef.h>
#include <string.h>
#include <math.h>

template <uint32_t HA, uint32_t HB> __device__ __forceinline__ void wg_n128(float (&d)[64], uint32_t descA, uint32_t descB, int scaleD) {
  asm volatile("{\n.reg .pred p;\n.reg .b64 da, db;\n"
    "mov.b64 da, {%64, %67};\nmov.b64 db, {%65, %68};\n"
    "setp.ne.b32 p, %66, 0;\n"
    "wgmma.mma_async.sync.aligned.m64n128k16.f32.bf16.bf16 "
    "{%0, %1, %2, %3, %4, %5, %6, %7, %8, %9, %10, %11, %12, %13, %14, %15, "
    "%16, %17, %18, %19, %20, %21, %22, %23, %24, %25, %26, %27, %28, %29, %30, %31, "
    "%32, %33, %34, %35, %36, %37, %38, %39, %40, %41, %42, %43, %44, %45, %46, %47, "
    "%48, %49, %50, %51, %52, %53, %54, %55, %56, %57, %58, %59, %60, %61, %62, %63}, "
    "da, db, p, 1, 1, 0, 1;\n}\n"
    : "+f"(d[0]), "+f"(d[1]), "+f"(d[2]), "+f"(d[3]), "+f"(d[4]), "+f"(d[5]), "+f"(d[6]), "+f"(d[7]),
      "+f"(d[8]), "+f"(d[9]), "+f"(d[10]), "+f"(d[11]), "+f"(d[12]), "+f"(d[13]), "+f"(d[14]), "+f"(d[15]),
      "+f"(d[16]), "+f"(d[17]), "+f"(d[18]), "+f"(d[19]), "+f"(d[20]), "+f"(d[21]), "+f"(d[22]), "+f"(d[23]),
      "+f"(d[24]), "+f"(d[25]), "+f"(d[26]), "+f"(d[27]), "+f"(d[28]), "+f"(d[29]), "+f"(d[30]), "+f"(d[31]),
      "+f"(d[32]), "+f"(d[33]), "+f"(d[34]), "+f"(d[35]), "+f"(d[36]), "+f"(d[37]), "+f"(d[38]), "+f"(d[39]),
      "+f"(d[40]), "+f"(d[41]), "+f"(d[42]), "+f"(d[43]), "+f"(d[44]), "+f"(d[45]), "+f"(d[46]), "+f"(d[47]),
      "+f"(d[48]), "+f"(d[49]), "+f"(d[50]), "+f"(d[51]), "+f"(d[52]), "+f"(d[53]), "+f"(d[54]), "+f"(d[55]),
      "+f"(d[56]), "+f"(d[57]), "+f"(d[58]), "+f"(d[59]), "+f"(d[60]), "+f"(d[61]), "+f"(d[62]), "+f"(d[63])
    : "r"(descA), "r"(descB), "r"(scaleD), "n"(HA), "n"(HB));
}
template <uint32_t HA, uint32_t HB> __device__ __forceinline__ void wg_n192(float (&d)[96], uint32_t descA, uint32_t descB, int scaleD) {
  asm volatile("{\n.reg .pred p;\n.reg .b64 da, db;\n"
    "mov.b64 da, {%96, %99};\nmov.b64 db, {%97, %100};\n"
    "setp.ne.b32 p, %98, 0;\n"
    "wgmma.mma_async.sync.aligned.m64n192k16.f32.bf16.bf16 "
    "{%0, %1, %2, %3, %4, %5, %6, %7, %8, %9, %10, %11, %12, %13, %14, %15, "
    "%16, %17, %18, %19, %20, %21, %22, %23, %24, %25, %26, %27, %28, %29, %30, %31, "
    "%32, %33, %34, %35, %36, %37, %38, %39, %40, %41, %42, %43, %44, %45, %46, %47, "
    "%48, %49, %50, %51, %52, %53, %54, %55, %56, %57, %58, %59, %60, %61, %62, %63, "
    "%64, %65, %66, %67, %68, %69, %70, %71, %72, %73, %74, %75, %76, %77, %78, %79, "
    "%80, %81, %82, %83, %84, %85, %86, %87, %88, %89, %90, %91, %92, %93, %94, %95}, "
    "da, db, p, 1, 1, 0, 1;\n}\n"
    : "+f"(d[0]), "+f"(d[1]), "+f"(d[2]), "+f"(d[3]), "+f"(d[4]), "+f"(d[5]), "+f"(d[6]), "+f"(d[7]),
      "+f"(d[8]), "+f"(d[9]), "+f"(d[10]), "+f"(d[11]), "+f"(d[12]), "+f"(d[13]), "+f"(d[14]), "+f"(d[15]),
      "+f"(d[16]), "+f"(d[17]), "+f"(d[18]), "+f"(d[19]), "+f"(d[20]), "+f"(d[21]), "+f"(d[22]), "+f"(d[23]),
      "+f"(d[24]), "+f"(d[25]), "+f"(d[26]), "+f"(d[27]), "+f"(d[28]), "+f"(d[29]), "+f"(d[30]), "+f"(d[31]),
      "+f"(d[32]), "+f"(d[33]), "+f"(d[34]), "+f"(d[35]), "+f"(d[36]), "+f"(d[37]), "+f"(d[38]), "+f"(d[39]),
      "+f"(d[40]), "+f"(d[41]), "+f"(d[42]), "+f"(d[43]), "+f"(d[44]), "+f"(d[45]), "+f"(d[46]), "+f"(d[47]),
      "+f"(d[48]), "+f"(d[49]), "+f"(d[50]), "+f"(d[51]), "+f"(d[52]), "+f"(d[53]), "+f"(d[54]), "+f"(d[55]),
      "+f"(d[56]), "+f"(d[57]), "+f"(d[58]), "+f"(d[59]), "+f"(d[60]), "+f"(d[61]), "+f"(d[62]), "+f"(d[63]),
      "+f"(d[64]), "+f"(d[65]), "+f"(d[66]), "+f"(d[67]), "+f"(d[68]), "+f"(d[69]), "+f"(d[70]), "+f"(d[71]),
      "+f"(d[72]), "+f"(d[73]), "+f"(d[74]), "+f"(d[75]), "+f"(d[76]), "+f"(d[77]), "+f"(d[78]), "+f"(d[79]),
      "+f"(d[80]), "+f"(d[81]), "+f"(d[82]), "+f"(d[83]), "+f"(d[84]), "+f"(d[85]), "+f"(d[86]), "+f"(d[87]),
      "+f"(d[88]), "+f"(d[89]), "+f"(d[90]), "+f"(d[91]), "+f"(d[92]), "+f"(d[93]), "+f"(d[94]), "+f"(d[95])
    : "r"(descA), "r"(descB), "r"(scaleD), "n"(HA), "n"(HB));
}
template <uint32_t HA, uint32_t HB> __device__ __forceinline__ void wg_n256(float (&d)[128], uint32_t descA, uint32_t descB, int scaleD) {
  asm volatile("{\n.reg .pred p;\n.reg .b64 da, db;\n"
    "mov.b64 da, {%128, %131};\nmov.b64 db, {%129, %132};\n"
    "setp.ne.b32 p, %130, 0;\n"
    "wgmma.mma_async.sync.aligned.m64n256k16.f32.bf16.bf16 "
    "{%0, %1, %2, %3, %4, %5, %6, %7, %8, %9, %10, %11, %12, %13, %14, %15, "
    "%16, %17, %18, %19, %20, %21, %22, %23, %24, %25, %26, %27, %28, %29, %30, %31, "
    "%32, %33, %34, %35, %36, %37, %38, %39, %40, %41, %42, %43, %44, %45, %46, %47, "
    "%48, %49, %50, %51, %52, %53, %54, %55, %56, %57, %58, %59, %60, %61, %62, %63, "
    "%64, %65, %66, %67, %68, %69, %70, %71, %72, %73, %74, %75, %76, %77, %78, %79, "
    "%80, %81, %82, %83, %84, %85, %86, %87, %88, %89, %90, %91, %92, %93, %94, %95, "
    "%96, %97, %98, %99, %100, %101, %102, %103, %104, %105, %106, %107, %108, %109, %110, %111, "
    "%112, %113, %114, %115, %116, %117, %118, %119, %120, %121, %122, %123, %124, %125, %126, %127}, "
    "da, db, p, 1, 1, 0, 1;\n}\n"
    : "+f"(d[0]), "+f"(d[1]), "+f"(d[2]), "+f"(d[3]), "+f"(d[4]), "+f"(d[5]), "+f"(d[6]), "+f"(d[7]),
      "+f"(d[8]), "+f"(d[9]), "+f"(d[10]), "+f"(d[11]), "+f"(d[12]), "+f"(d[13]), "+f"(d[14]), "+f"(d[15]),
      "+f"(d[16]), "+f"(d[17]), "+f"(d[18]), "+f"(d[19]), "+f"(d[20]), "+f"(d[21]), "+f"(d[22]), "+f"(d[23]),
      "+f"(d[24]), "+f"(d[25]), "+f"(d[26]), "+f"(d[27]), "+f"(d[28]), "+f"(d[29]), "+f"(d[30]), "+f"(d[31]),
      "+f"(d[32]), "+f"(d[33]), "+f"(d[34]), "+f"(d[35]), "+f"(d[36]), "+f"(d[37]), "+f"(d[38]), "+f"(d[39]),
      "+f"(d[40]), "+f"(d[41]), "+f"(d[42]), "+f"(d[43]), "+f"(d[44]), "+f"(d[45]), "+f"(d[46]), "+f"(d[47]),
      "+f"(d[48]), "+f"(d[49]), "+f"(d[50]), "+f"(d[51]), "+f"(d[52]), "+f"(d[53]), "+f"(d[54]), "+f"(d[55]),
      "+f"(d[56]), "+f"(d[57]), "+f"(d[58]), "+f"(d[59]), "+f"(d[60]), "+f"(d[61]), "+f"(d[62]), "+f"(d[63]),
      "+f"(d[64]), "+f"(d[65]), "+f"(d[66]), "+f"(d[67]), "+f"(d[68]), "+f"(d[69]), "+f"(d[70]), "+f"(d[71]),
      "+f"(d[72]), "+f"(d[73]), "+f"(d[74]), "+f"(d[75]), "+f"(d[76]), "+f"(d[77]), "+f"(d[78]), "+f"(d[79]),
      "+f"(d[80]), "+f"(d[81]), "+f"(d[82]), "+f"(d[83]), "+f"(d[84]), "+f"(d[85]), "+f"(d[86]), "+f"(d[87]),
      "+f"(d[88]), "+f"(d[89]), "+f"(d[90]), "+f"(d[91]), "+f"(d[92]), "+f"(d[93]), "+f"(d[94]), "+f"(d[95]),
      "+f"(d[96]), "+f"(d[97]), "+f"(d[98]), "+f"(d[99]), "+f"(d[100]), "+f"(d[101]), "+f"(d[102]), "+f"(d[103]),
      "+f"(d[104]), "+f"(d[105]), "+f"(d[106]), "+f"(d[107]), "+f"(d[108]), "+f"(d[109]), "+f"(d[110]), "+f"(d[111]),
      "+f"(d[112]), "+f"(d[113]), "+f"(d[114]), "+f"(d[115]), "+f"(d[116]), "+f"(d[117]), "+f"(d[118]), "+f"(d[119]),
      "+f"(d[120]), "+f"(d[121]), "+f"(d[122]), "+f"(d[123]), "+f"(d[124]), "+f"(d[125]), "+f"(d[126]), "+f"(d[127])
    : "r"(descA), "r"(descB), "r"(scaleD), "n"(HA), "n"(HB));
}

namespace {

constexpr int S_ = 2048, D_ = 1024, F_ = 3584;
constexpr int NCTA = 128;
constexpr int NTHREADS = 384;

constexpr uint32_t W_OFF      = 6 * 16384;
constexpr uint32_t BAR_OFF    = W_OFF + 16 * 8192;
constexpr uint32_t PAR_OFF    = BAR_OFF + 1280;
constexpr uint32_t SMEM_BYTES = 232448, SMEM_BASE = 1024;
constexpr uint32_t SL_OFF     = W_OFF + 11 * 8192;
constexpr uint32_t TAB_OFF    = W_OFF + 15 * 8192;
constexpr uint32_t B_R = 1024, B_PAR = 1072, B_SL = 1120, B_SLE = 1088, B_Q = 1096, B_ST = 1152, B_GB = 1056, B_XB = 1168, B_END = 1184, ROLE_OFF = 1272;

constexpr uint32_t H128 = 0x40000040u;
constexpr uint32_t H64  = 0x80000020u;

constexpr int N_W = 138, N_HK = 3, N_END = 130;
__constant__ uint2 c_cons[2][135] = {
  {
    {0x0,0x84580800}, {0x6000400,0x84580808}, {0x18000800,0x84580810}, {0x12000c00,0x84580818}, {0xc001000,0x84580820}, {0x0,0x84580828},
    {0x6000400,0x84580830}, {0x18000800,0x84580838}, {0x12000c00,0x84580840}, {0xc000000,0x84580848}, {0x800,0x84580850}, {0x6000c00,0x84580858},
    {0x18000000,0x84580860}, {0x12000800,0x84580868}, {0xc000c00,0x84580870}, {0x0,0x84580878}, {0x400,0x84580880}, {0x400,0x84580888},
    {0x18001000,0x4500890}, {0x1c000000,0x84580898}, {0x14000800,0x845818a0}, {0xc001400,0x41008a8}, {0x10000c00,0x845818b0}, {0x1000,0x41808b8},
    {0x4000000,0x845808c0}, {0x8000800,0x845808c8}, {0x1400,0x845808d0}, {0x1400,0x845808d8}, {0x18000000,0x3b808e0}, {0xc000800,0x845808e8},
    {0x12001400,0x845808f0}, {0xc00,0x845808f8}, {0x6001000,0x84580c00}, {0x18000400,0x84580c08}, {0xc000000,0x84580c10}, {0x12000800,0x84580c18},
    {0x1400,0x84580c20}, {0x6000c00,0x84580c28}, {0x18000400,0x84580c30}, {0xc000800,0x84580c38}, {0x12000c00,0x84580c40}, {0x400,0x84580c48},
    {0x6000800,0x84580c50}, {0x18000c00,0x84580c58}, {0x0,0x3d80c60}, {0x1400,0x83500c68}, {0x4000c00,0x84580c70}, {0x8001000,0x84580c78},
    {0x18000400,0x84580c80}, {0xc000000,0x84580c88}, {0x10000800,0x84580c90}, {0x14000c00,0x84580c98}, {0x1c000400,0x84580ca0}, {0x800,0x84580ca8},
    {0x4000c00,0x84580cb0}, {0x8000400,0x84580cb8}, {0x18000800,0x84580cc0}, {0xc000c00,0x84580cc8}, {0x10000400,0x84580cd0}, {0x14000800,0x84580cd8},
    {0x1c000c00,0x84580ce0}, {0x1000,0x83d80ce8}, {0x4000400,0x84580cf0}, {0x8000000,0x84580cf8}, {0x18000800,0x84580800}, {0xc001400,0x84580808},
    {0x10000c00,0x84580810}, {0x14000400,0x84580818}, {0x1c000800,0x84580820}, {0xc00,0x84580828}, {0x4000400,0x84580830}, {0x8000800,0x84580838},
    {0x18000c00,0x84580840}, {0xc000400,0x84580848}, {0x10000800,0x84580850}, {0x14000c00,0x84580858}, {0x1c000400,0x84580860}, {0x0,0x3580868},
    {0x4000800,0x84580870}, {0x8001400,0x84580878}, {0x18000c00,0x84580880}, {0xc001000,0x84580888}, {0x10000400,0x84580890}, {0x14000000,0x84580898},
    {0x1c000800,0x845808a0}, {0x1400,0x845808a8}, {0x4000c00,0x845808b0}, {0x8001000,0x845808b8}, {0x18000400,0x845808c0}, {0xc000000,0x845808c8},
    {0x10000800,0x845808d0}, {0x14001400,0x845808d8}, {0x1c000c00,0x845808e0}, {0x1000,0x845808e8}, {0x4000400,0x845808f0}, {0x8000000,0x845808f8},
    {0x18000800,0x84580c00}, {0xc001400,0x84580c08}, {0x10000c00,0x84580c10}, {0x14001000,0x84580c18}, {0x1c000400,0x84580c20}, {0x0,0x84580c28},
    {0x4000800,0x84580c30}, {0x8001400,0x84580c38}, {0x18000c00,0x84580c40}, {0xc001000,0x84580c48}, {0x10000400,0x84580c50}, {0x14000000,0x84580c58},
    {0x1c000800,0x84580c60}, {0x1400,0x84580c68}, {0x4000c00,0x84580c70}, {0x8001000,0x84580c78}, {0x18000400,0x84580c80}, {0xc000000,0x84580c88},
    {0x10000800,0x84580c90}, {0x14001400,0x84580c98}, {0x1c000c00,0x84580ca0}, {0x1000,0x84580ca8}, {0x4000400,0x84580cb0}, {0x8000000,0x84580cb8},
    {0x18000800,0x84580cc0}, {0xc001400,0x84580cc8}, {0x10000c00,0x84580cd0}, {0x14001000,0x84580cd8}, {0x1c000400,0x84580ce0}, {0x0,0x84580ce8},
    {0x4000800,0x84580cf0}, {0x8001400,0x84580cf8}, {0x18000c00,0x84580800}, {0xc001000,0x84580808}, {0x400,0x84580010}, {0x0,0x84580018},
    {0x14000800,0x0}, {0x14000800,0x0}, {0x14000800,0x0},
  },
  {
    {0x6001400,0x300900}, {0x18001000,0x380908}, {0x12000400,0x400910}, {0xc001400,0x480918}, {0x1000,0x500920}, {0x6000400,0x580928},
    {0x18001400,0x600930}, {0x12001000,0x680938}, {0xc000800,0x4480940}, {0x1400,0x84581948}, {0x6000c00,0x4001950}, {0x18001000,0x4080958},
    {0x12000000,0x84580960}, {0xc000800,0x84580968}, {0x1400,0x84580970}, {0x6000c00,0x84580978}, {0x400,0x84580980}, {0x400,0x84580988},
    {0x18000c00,0x2b80990}, {0x1c001000,0x84580998}, {0x14000400,0x845809a0}, {0xc000000,0x845809a8}, {0x10000800,0x845809b0}, {0x1400,0x845809b8},
    {0x4000c00,0xc009c0}, {0x8001000,0xc809c8}, {0x400,0x845809d0}, {0x400,0x845809d8}, {0x12001000,0x821809e0}, {0x0,0x822009e8},
    {0x6001400,0x822809f0}, {0x18001000,0x823009f8}, {0xc000000,0x82380d00}, {0x12001400,0x82400d08}, {0x1000,0x82500d10}, {0x6000400,0x84580d18},
    {0x18000000,0x82580d20}, {0xc000800,0x84580d28}, {0x12001400,0x84580d30}, {0xc00,0x84580d38}, {0x6001000,0x84580d40}, {0x18000400,0x84580d48},
    {0xc000000,0x84580d50}, {0x12000800,0x84580d58}, {0x0,0x82600d60}, {0x1400,0x82680d68}, {0x4001000,0x82700d70}, {0x8000000,0x82780d78},
    {0x18001400,0x82800d80}, {0xc001000,0x82880d88}, {0x10000000,0x82900d90}, {0x14001400,0x82980d98}, {0x1c001000,0x82a00da0}, {0x0,0x82a80da8},
    {0x4001400,0x82b00db0}, {0x8001000,0x82d80db8}, {0x18000400,0x84580dc0}, {0xc000000,0x84580dc8}, {0x10000800,0x84580dd0}, {0x14001400,0x84580dd8},
    {0x1c000c00,0x82e00de0}, {0x1000,0x82e80de8}, {0x4000000,0x82f00df0}, {0x8001400,0x82f80df8}, {0x18001000,0x2000900}, {0xc000000,0x2080908},
    {0x10001400,0x2100910}, {0x14001000,0x2180918}, {0x1c000000,0x2200920}, {0x1400,0x2280928}, {0x4001000,0x2300930}, {0x8000000,0x2580938},
    {0x18000800,0x84580940}, {0xc001400,0x84580948}, {0x10000c00,0x84580950}, {0x14001000,0x84580958}, {0x1c000400,0x2600960}, {0x0,0x2680968},
    {0x4000800,0x2700970}, {0x8001400,0x2780978}, {0x18000c00,0x2800980}, {0xc001000,0x2880988}, {0x10000400,0x2900990}, {0x14000000,0x2980998},
    {0x1c000800,0x2a009a0}, {0x1400,0x2a809a8}, {0x4000c00,0x2b009b0}, {0x8001000,0x2b809b8}, {0x18000400,0x2c009c0}, {0xc000000,0x2c809c8},
    {0x10000800,0x2d009d0}, {0x14001400,0x2d809d8}, {0x1c000c00,0x2e009e0}, {0x1000,0x2e809e8}, {0x4000400,0x2f009f0}, {0x8000000,0x2f809f8},
    {0x18000800,0x82000d00}, {0xc001400,0x82080d08}, {0x10000c00,0x82100d10}, {0x14001000,0x82180d18}, {0x1c000400,0x82200d20}, {0x0,0x82280d28},
    {0x4000800,0x82300d30}, {0x8001400,0x82380d38}, {0x18000c00,0x82400d40}, {0xc001000,0x82480d48}, {0x10000400,0x82500d50}, {0x14000000,0x82580d58},
    {0x1c000800,0x82600d60}, {0x1400,0x82680d68}, {0x4000c00,0x82700d70}, {0x8001000,0x82780d78}, {0x18000400,0x82800d80}, {0xc000000,0x82880d88},
    {0x10000800,0x82900d90}, {0x14001400,0x82980d98}, {0x1c000c00,0x82a00da0}, {0x1000,0x82a80da8}, {0x4000400,0x82b00db0}, {0x8000000,0x82b80db8},
    {0x18000800,0x82c00dc0}, {0xc001400,0x82c80dc8}, {0x10000c00,0x82d00dd0}, {0x14001000,0x82d80dd8}, {0x1c000400,0x82e00de0}, {0x0,0x82e80de8},
    {0x4000800,0x20005f0}, {0x8001400,0x845805f8}, {0x18000c00,0x84580100}, {0xc001000,0x2080108}, {0x400,0x84580110}, {0x0,0x84580118},
    {0x14000800,0x0}, {0x14000800,0x0}, {0x14000800,0x0},
  },
};
__constant__ uint2 c_act[2][135] = {
  {
    {0x81000458,0xa0000000}, {0x80004458,0xa0004008}, {0x80008458,0xa0008010}, {0x8000c458,0xa000c018}, {0x80010458,0xa0010020}, {0x14200,0xa0000028},
    {0x18208,0xa0004030}, {0x1c210,0xa0008038}, {0x3020218,0xa000c040}, {0x24228,0xa0000048}, {0x28238,0xa0008050}, {0x2c240,0xa000c058},
    {0x30248,0xa0000060}, {0x34250,0xa0008068}, {0x38258,0xa000c070}, {0x3c260,0xa0000078}, {0x328,0x4080}, {0x280,0x40004088},
    {0x5080358,0x80010090}, {0x88360,0x80000098}, {0x90368,0x800080a0}, {0x98370,0x800140a8}, {0xa0378,0x8000c0b0}, {0xa8290,0x800100b8},
    {0xb0298,0x800000c0}, {0xb82a0,0x800080c8}, {0x2a8,0x140d0}, {0x80000458,0x400140d8}, {0x70003a8,0xa00000e0}, {0x43b0,0xa00080e8},
    {0x83b8,0xa00140f0}, {0xc3c0,0xa000c0f8}, {0x103c8,0xa0010000}, {0x143d8,0xa0004008}, {0x182e0,0xa0000010}, {0x1c2e8,0xa0008018},
    {0x202f0,0xa0014020}, {0x242f8,0xa000c028}, {0x80028208,0xa0004030}, {0x8002c218,0xa0008038}, {0x80030228,0xa000c040}, {0x80034230,0xa0004048},
    {0x80038238,0xa0008050}, {0x8003c240,0xa000c058}, {0x80000458,0x20000060}, {0x80000330,0x80014068}, {0x80004338,0x8000c070}, {0x80008340,0x80010078},
    {0x8000c348,0x80004080}, {0x80010350,0x80000088}, {0x80014358,0x80008090}, {0x80018270,0x8000c098}, {0x8001c280,0x800040a0}, {0x80020290,0x800080a8},
    {0x80024298,0x8000c0b0}, {0x800282a0,0x800040b8}, {0x8002c2a8,0x800080c0}, {0x800302b0,0x8000c0c8}, {0x800342b8,0x800040d0}, {0x800382c0,0x800080d8},
    {0x8003c2c8,0x8000c0e0}, {0x800003b8,0x800100e8}, {0x800043c0,0x800040f0}, {0x800083c8,0x800000f8}, {0x8000c3d0,0x80008000}, {0x800103d8,0x80014008},
    {0x800143e0,0x8000c010}, {0x800182f0,0x80004018}, {0x1c200,0x80008020}, {0x20210,0x8000c028}, {0x24218,0x80004030}, {0x28220,0x80008038},
    {0x2c228,0x8000c040}, {0x30230,0x80004048}, {0x34238,0x80008050}, {0x38240,0x8000c058}, {0x3c248,0x80004060}, {0x918c338,0x60000068},
    {0x190340,0x60008070}, {0x194348,0x60014078}, {0x198350,0x6000c080}, {0x19c358,0x60010088}, {0x1a0360,0x60004090}, {0x1a4268,0x60000098},
    {0x1a8270,0x600080a0}, {0x1ac278,0x600140a8}, {0x1b0280,0x6000c0b0}, {0x1b4288,0x600100b8}, {0x1b8290,0x600040c0}, {0x1bc298,0x600000c8},
    {0x1c02a0,0x600080d0}, {0x1c42a8,0x600140d8}, {0x1c82b0,0x6000c0e0}, {0x1cc2b8,0x600100e8}, {0x1d02c0,0x600040f0}, {0x1d42c8,0x600000f8},
    {0x1d82d0,0x60008000}, {0x1dc2d8,0x60014008}, {0xb1e02e0,0x6000c010}, {0x1e42e8,0x60010018}, {0x1e82f0,0x60004020}, {0x1ec2f8,0x60000028},
    {0x801f0200,0x60008030}, {0x801f4208,0x60014038}, {0x801f8210,0x6000c040}, {0x801fc218,0x60010048}, {0x80200220,0x60004050}, {0x80204228,0x60000058},
    {0x80208230,0x60008060}, {0x8020c238,0x60014068}, {0x80210240,0x6000c070}, {0x80214248,0x60010078}, {0x80218250,0x60004080}, {0x8021c258,0x60000088},
    {0x8d220260,0x60008090}, {0x80224268,0x60014098}, {0x80228270,0x6000c0a0}, {0x8022c278,0x600100a8}, {0x80230280,0x600040b0}, {0x80234288,0x600000b8},
    {0x80238290,0x600080c0}, {0x8023c298,0x600140c8}, {0x802402a0,0x6000c0d0}, {0x802442a8,0x600100d8}, {0x802482b0,0x600040e0}, {0x8024c2b8,0x600000e8},
    {0x802502c0,0x600080f0}, {0x802542c8,0x600140f8}, {0x802582d0,0x6000c000}, {0x8025c2d8,0x60010008}, {0x801002e0,0x20004010}, {0x801042e8,0x20000018},
    {0x0,0x0}, {0x0,0x0}, {0x0,0x0},
  },
  {
    {0x91058458,0x40014100}, {0x5c220,0x40010108}, {0x60230,0x40004110}, {0x64300,0x40014118}, {0x68308,0x40010120}, {0x6c310,0x40004128},
    {0x70318,0x40014130}, {0x74320,0x40010138}, {0x78268,0x40008140}, {0x7c330,0x40014148}, {0x40270,0xa000c150}, {0x44338,0xa0010158},
    {0x48278,0xa0000160}, {0x4c340,0xa0008168}, {0x50348,0xa0014170}, {0x54350,0xa000c178}, {0x288,0x4180}, {0x380,0x40004188},
    {0x150c02b0,0x4000c190}, {0xc82b8,0x40010198}, {0xd0388,0x400041a0}, {0xd82c0,0x400001a8}, {0xe02c8,0x400081b0}, {0xe82d8,0x400141b8},
    {0xf0390,0x4000c1c0}, {0xf8398,0x400101c8}, {0x3a0,0x41d0}, {0x80000458,0x400041d8}, {0x9705c200,0x400101e0}, {0x80060210,0x400001e8},
    {0x80064220,0x400141f0}, {0x683e0,0x400101f8}, {0x6c3e8,0x40000100}, {0x703f0,0x40014108}, {0x743f8,0x40010110}, {0x80078248,0x40004118},
    {0x8007c300,0x40000120}, {0x80040250,0xa0008128}, {0x80044308,0xa0014130}, {0x80048258,0xa000c138}, {0x8004c310,0xa0010140}, {0x80050318,0xa0004148},
    {0x80054320,0xa0000150}, {0x80058328,0xa0008158}, {0x80000458,0x20000160}, {0x80040268,0x40014168}, {0x80044278,0x40010170}, {0x80048288,0x40000178},
    {0x8004c368,0x40014180}, {0x80050370,0x40010188}, {0x80054378,0x40000190}, {0x80058380,0x40014198}, {0x8005c388,0x400101a0}, {0x80060390,0x400001a8},
    {0x80064398,0x400141b0}, {0x800683a0,0x400101b8}, {0x8006c2d0,0x400041c0}, {0x800703a8,0x400001c8}, {0x800742d8,0x400081d0}, {0x800783b0,0x400141d8},
    {0x8007c2e0,0x4000c1e0}, {0x800402e8,0x400101e8}, {0x800442f8,0x400001f0}, {0x48208,0x400141f8}, {0x8004c3e8,0x40010100}, {0x800503f0,0x40000108},
    {0x800543f8,0x40014110}, {0x58300,0x40010118}, {0x5c308,0x40000120}, {0x60310,0x40014128}, {0x64318,0x40010130}, {0x68320,0x40000138},
    {0x6c250,0x40008140}, {0x70328,0x40014148}, {0x74258,0x4000c150}, {0x78330,0x40010158}, {0x7c260,0x40004160}, {0x918c338,0x20000168},
    {0x190340,0x20008170}, {0x194348,0x20014178}, {0x198350,0x2000c180}, {0x19c358,0x20010188}, {0x1a0360,0x20004190}, {0x1a4368,0x20000198},
    {0x1a8370,0x200081a0}, {0x1ac378,0x200141a8}, {0x1b0380,0x2000c1b0}, {0x1b4388,0x200101b8}, {0x1b8390,0x200041c0}, {0x1bc398,0x200001c8},
    {0x1c03a0,0x200081d0}, {0x1c43a8,0x200141d8}, {0x1c83b0,0x2000c1e0}, {0x1cc3b8,0x200101e8}, {0x1d03c0,0x200041f0}, {0x1d43c8,0x200001f8},
    {0x1d83d0,0x20008100}, {0x1dc3d8,0x20014108}, {0xb1e03e0,0x2000c110}, {0x1e43e8,0x20010118}, {0x1e83f0,0x20004120}, {0x1ec3f8,0x20000128},
    {0x801f0300,0x20008130}, {0x801f4308,0x20014138}, {0x801f8310,0x2000c140}, {0x801fc318,0x20010148}, {0x80200320,0x20004150}, {0x80204328,0x20000158},
    {0x80208330,0x20008160}, {0x8020c338,0x20014168}, {0x80210340,0x2000c170}, {0x80214348,0x20010178}, {0x80218350,0x20004180}, {0x8021c358,0x20000188},
    {0x8d220360,0x20008190}, {0x80224368,0x20014198}, {0x80228370,0x2000c1a0}, {0x8022c378,0x200101a8}, {0x80230380,0x200041b0}, {0x80234388,0x200001b8},
    {0x80238390,0x200081c0}, {0x8023c398,0x200141c8}, {0x802403a0,0x2000c1d0}, {0x802443a8,0x200101d8}, {0x802483b0,0x200041e0}, {0x8024c3b8,0x200001e8},
    {0x802503c0,0x200081f0}, {0x802543c8,0x200141f8}, {0x802583d0,0x2000c100}, {0x8025c3d8,0x20010108}, {0x801003e0,0x20004110}, {0x801043e8,0x20000118},
    {0x0,0x0}, {0x0,0x0}, {0x0,0x0},
  },
};
__constant__ uint2 c_w[1][139] = {
  {
    {0x84580000,0x20000}, {0x84580000,0x2026008}, {0x84580000,0x4038010}, {0x84580000,0x6032018}, {0x84580000,0x802c020}, {0x2000000,0xa000028},
    {0x2080000,0xc006030}, {0x2100000,0xe018038}, {0x2180000,0x10012040}, {0x2200000,0x1200c048}, {0x2280000,0x14000050}, {0x2300300,0x16006058},
    {0x2380308,0x18018060}, {0x2400310,0x1a012068}, {0x2480318,0x1c00c070}, {0x2500320,0x1e000078}, {0x2580328,0x6150}, {0x2600330,0x2018158},
    {0x2680338,0x4012160}, {0x2700340,0x600c168}, {0x2780348,0x8000170}, {0x3500000,0xa026178}, {0x3580000,0x18890}, {0x84580000,0x401c898},
    {0x3600000,0x80148a0}, {0x3680000,0xc00c8a8}, {0x84580000,0x100108b0}, {0x3700000,0x140008b8}, {0x3780000,0x180048c0}, {0x84580000,0x1c0288c8},
    {0x3980000,0x184e0}, {0x3b00000,0x200c4e8}, {0x84580000,0x40124f0}, {0x2c003c0,0x60004f8}, {0x2c803c8,0x8006400}, {0x2e00000,0xa018408},
    {0x2e80000,0xc00c410}, {0x2f00000,0xe012418}, {0x2f80000,0x10000420}, {0x82000000,0x12006428}, {0x82080000,0x14018430}, {0x82100000,0x1600c438},
    {0x3e00000,0x18012440}, {0x3e80000,0x1a000448}, {0x3f00000,0x1c006450}, {0x3f80000,0x1e018458}, {0x83000000,0xc528}, {0x83080000,0x2012530},
    {0x83100000,0x4000538}, {0x83180000,0x6006540}, {0x83200000,0x8018548}, {0x83280000,0xa00c550}, {0x83300000,0xc032558}, {0x83380000,0xc68},
    {0x83400000,0x2004c70}, {0x84580000,0x4008c78}, {0x83480000,0x6018c80}, {0x83500000,0x800cc88}, {0x83580000,0xa010c90}, {0x84580000,0xc014c98},
    {0x83600000,0xe01cca0}, {0x83680000,0x10000ca8}, {0x83700000,0x12004cb0}, {0x83780000,0x14008cb8}, {0x83800000,0x16018cc0}, {0x83880000,0x1800ccc8},
    {0x83900000,0x1a010cd0}, {0x83980000,0x1c014cd8}, {0x83a00000,0x1e03cce0}, {0x83a80000,0x10e8}, {0x83b00000,0x20050f0}, {0x83b80000,0x40090f8},
    {0x83c00000,0x6019000}, {0x83c80000,0x800d008}, {0x83d00000,0xa011010}, {0x83d80000,0xc015018}, {0x83e00000,0xe01d020}, {0x83e80000,0x10001028},
    {0x83f00000,0x12005030}, {0x83f80000,0x14009038}, {0x3000000,0x16019040}, {0x3080000,0x1800d048}, {0x3100000,0x1a011050}, {0x3180000,0x1c015058},
    {0x3200000,0x1e03d060}, {0x3280000,0x6001468}, {0x3300000,0x8005470}, {0x3380000,0xa009478}, {0x3400000,0xc019480}, {0x3480000,0xe00d488},
    {0x3500000,0x10011490}, {0x3580000,0x12015498}, {0x3600000,0x1401d4a0}, {0x3680000,0x160014a8}, {0x3700000,0x180054b0}, {0x3780000,0x1a0094b8},
    {0x3800000,0x1c0194c0}, {0x3880000,0x1e00d4c8}, {0x3900000,0x200114d0}, {0x3980000,0x220154d8}, {0x3a00000,0x2401d4e0}, {0x3a80000,0x260014e8},
    {0x3b00000,0x280054f0}, {0x3b80000,0x2a0094f8}, {0x3c00000,0x2c019400}, {0x3c80000,0x2e00d408}, {0x3d00000,0x30011410}, {0x3d80000,0x32015418},
    {0x3e00000,0x3401d420}, {0x3e80000,0x36001428}, {0x3f00000,0x38005430}, {0x3f80000,0x3a009438}, {0x83000000,0x3c019440}, {0x83080000,0x3e00d448},
    {0x83100000,0x40011450}, {0x83180000,0x42015458}, {0x83200000,0x4401d460}, {0x83280000,0x46001468}, {0x83300000,0x48005470}, {0x83380000,0x4a009478},
    {0x83400000,0x4c019480}, {0x83480000,0x4e00d488}, {0x83500000,0x50011490}, {0x83580000,0x52015498}, {0x83600000,0x5401d4a0}, {0x83680000,0x560014a8},
    {0x83700000,0x580054b0}, {0x83780000,0x5a0094b8}, {0x83800000,0x5c0194c0}, {0x83880000,0x5e00d4c8}, {0x83900000,0x600114d0}, {0x83980000,0x620154d8},
    {0x83a00000,0x6401d4e0}, {0x83a80000,0x660014e8}, {0x83b00000,0x680054f0}, {0x83b80000,0x6a0094f8}, {0x83c00000,0x6c019400}, {0x83c80000,0x6e02d408},
    {0x0,0x0},
  },
};

constexpr int T_H = 0, T_O = 32, T_X1 = 64, T_ACT = 96, N_TILES = 208;
constexpr int G_H0 = 0, G_H1 = 1, G_O = 2, G_H2 = 3, G_ACT = 4, G_X1 = 7, G_HK = 15;

struct Scratch {
  uint4 img[8 * N_TILES * 1024];
  uint32_t mod0[4 * 4 * 512];
  uint32_t modp[4096];
  uint2 stat[32 * 8 * 64];
  uint4 halo[16 * 16 * 128];
  uint32_t cnt[8 * 32];
  uint32_t ep[(NCTA + 4) * 32];
};
__device__ __align__(1024) Scratch g_s;

struct Ptrs {
  const __nv_bfloat16 *x, *c;
  Scratch* s;
  __nv_bfloat16* out;
};
struct Params {
  CUtensorMap mWqkv, mWo, mWg, mWu, mWd, mOut, mWm2, mX;
};

__device__ __forceinline__ uint32_t smem_u32(const void* p) { return (uint32_t)__cvta_generic_to_shared(p); }
__device__ __forceinline__ void mbar_init(uint32_t bar, uint32_t cnt) { asm volatile("mbarrier.init.shared::cta.b64 [%0], %1;" ::"r"(bar), "r"(cnt)); }
__device__ __forceinline__ void mbar_expect_tx(uint32_t bar, uint32_t bytes) { asm volatile("mbarrier.arrive.expect_tx.shared::cta.b64 _, [%0], %1;" ::"r"(bar), "r"(bytes) : "memory"); }
__device__ __forceinline__ void mbar_arrive(uint32_t bar) { asm volatile("mbarrier.arrive.shared::cta.b64 _, [%0];" ::"r"(bar) : "memory"); }
__device__ __forceinline__ void mbar_arrive_remote(uint32_t bar_cluster) { asm volatile("mbarrier.arrive.shared::cluster.b64 _, [%0];" ::"r"(bar_cluster) : "memory"); }
__device__ __forceinline__ uint32_t mapa(uint32_t a, uint32_t cta) { uint32_t r; asm volatile("mapa.shared::cluster.u32 %0, %1, %2;" : "=r"(r) : "r"(a), "r"(cta)); return r; }
__device__ __forceinline__ void mbar_wait(uint32_t bar, uint32_t parity) {
  asm volatile("{\n.reg .pred p;\nW: mbarrier.try_wait.parity.shared::cta.b64 p, [%0], %1;\n@!p bra W;\n}" ::"r"(bar), "r"(parity) : "memory");
}
__device__ __forceinline__ void mbar_wait_bounded(uint32_t bar, uint32_t parity) {
  asm volatile("{\n.reg .pred p;\n.reg .u32 c;\nmov.u32 c, 0;\n"
               "W: mbarrier.try_wait.parity.shared::cta.b64 p, [%0], %1;\n@p bra D;\n"
               "add.u32 c, c, 1;\nsetp.lt.u32 p, c, 0x200000;\n@p bra W;\ntrap;\nD:\n}" ::"r"(bar), "r"(parity) : "memory");
}
constexpr uint32_t POLL_MAX = 1u << 20;
__device__ __forceinline__ void guard(uint32_t it) { asm volatile("{\n.reg .pred p;\nsetp.gt.u32 p, %0, 0x100000;\n@p trap;\n}" ::"r"(it)); }
__device__ __forceinline__ bool mbar_test(uint32_t bar, uint32_t parity) {
  uint32_t p; asm volatile("{\n.reg .pred P;\nmbarrier.test_wait.parity.shared::cta.b64 P, [%1], %2;\nselp.u32 %0, 1, 0, P;\n}" : "=r"(p) : "r"(bar), "r"(parity) : "memory"); return p;
}
__device__ __forceinline__ bool elect_one() {
  uint32_t p; asm volatile("{\n.reg .pred P;\nelect.sync _|P, 0xffffffff;\nselp.u32 %0, 1, 0, P;\n}" : "=r"(p)); return p;
}
__device__ __forceinline__ bool only_one() { asm volatile("{\n.reg .pred P;\nelect.sync _|P, 0xffffffff;\n@!P exit;\n}" ::: "memory"); return true; }
__device__ __forceinline__ void tma2d(uint32_t dst, const CUtensorMap* m, uint32_t bar, int c0, int c1) {
  asm volatile("cp.async.bulk.tensor.2d.shared::cluster.global.mbarrier::complete_tx::bytes [%0], [%1, {%3, %4}], [%2];" ::"r"(dst), "l"(m), "r"(bar), "r"(c0), "r"(c1) : "memory");
}
__device__ __forceinline__ uint64_t evict_first() { uint64_t p; asm("createpolicy.fractional.L2::evict_first.b64 %0, 1.0;" : "=l"(p)); return p; }
__device__ __forceinline__ void tma2d_once(uint32_t dst, const CUtensorMap* m, uint32_t bar, int c0, int c1) {
  asm volatile("cp.async.bulk.tensor.2d.shared::cluster.global.mbarrier::complete_tx::bytes.L2::cache_hint [%0], [%1, {%3, %4}], [%2], %5;" ::"r"(dst), "l"(m), "r"(bar), "r"(c0), "r"(c1), "l"(evict_first()) : "memory");
}
__device__ __forceinline__ void tma5d_once(uint32_t dst, const CUtensorMap* m, uint32_t bar, int c0, int c4) {
  asm volatile("cp.async.bulk.tensor.5d.shared::cluster.global.mbarrier::complete_tx::bytes.L2::cache_hint [%0], [%1, {%3, %5, %5, %5, %4}], [%2], %6;" ::"r"(dst), "l"(m), "r"(bar), "r"(c0), "r"(c4), "r"(0), "l"(evict_first()) : "memory");
}
__device__ __forceinline__ void tma5d(uint32_t dst, const CUtensorMap* m, uint32_t bar, int c0, int c4) {
  asm volatile("cp.async.bulk.tensor.5d.shared::cluster.global.mbarrier::complete_tx::bytes [%0], [%1, {%3, %5, %5, %5, %4}], [%2];" ::"r"(dst), "l"(m), "r"(bar), "r"(c0), "r"(c4), "r"(0) : "memory");
}
__device__ __forceinline__ void tma2d_st(const CUtensorMap* m, uint32_t src, int c0, int c1) {
  asm volatile("cp.async.bulk.tensor.2d.global.shared::cta.bulk_group [%0, {%2, %3}], [%1];" ::"l"(m), "r"(src), "r"(c0), "r"(c1) : "memory");
}
__device__ __forceinline__ void bulk_g2s(uint32_t dst, const void* src, uint32_t bytes, uint32_t bar) {
  asm volatile("cp.async.bulk.shared::cluster.global.mbarrier::complete_tx::bytes [%0], [%1], %2, [%3];" ::"r"(dst), "l"(src), "r"(bytes), "r"(bar) : "memory");
}
__device__ __forceinline__ void bulk_g2s_mc(uint32_t dst, const void* src, uint32_t bytes, uint32_t bar) {
  asm volatile("cp.async.bulk.shared::cluster.global.mbarrier::complete_tx::bytes.multicast::cluster [%0], [%1], %2, [%3], %4;" ::"r"(dst), "l"(src), "r"(bytes), "r"(bar), "h"((uint16_t)3) : "memory");
}
__device__ __forceinline__ void st_async(uint32_t dst, uint32_t bar, uint32_t a, uint32_t b, uint32_t c, uint32_t d) {
  asm volatile("st.async.weak.shared::cluster.mbarrier::complete_tx::bytes.v4.b32 [%0], {%2,%3,%4,%5}, [%1];" ::"r"(dst), "r"(bar), "r"(a), "r"(b), "r"(c), "r"(d) : "memory");
}
__device__ __forceinline__ void bulk_commit() { asm volatile("cp.async.bulk.commit_group;" ::: "memory"); }
__device__ __forceinline__ void bulk_wait_read() { asm volatile("cp.async.bulk.wait_group.read 0;" ::: "memory"); }
__device__ __forceinline__ void fence_async_smem() { asm volatile("fence.proxy.async.shared::cta;" ::: "memory"); }
__device__ __forceinline__ void fence_async_glob() { asm volatile("fence.proxy.async.global;" ::: "memory"); }
__device__ __forceinline__ void prefetch_tmap(const CUtensorMap* m) { asm volatile("prefetch.tensormap [%0];" ::"l"(m) : "memory"); }
__device__ __forceinline__ void wg_fence() { asm volatile("wgmma.fence.sync.aligned;" ::: "memory"); }
__device__ __forceinline__ void wg_commit() { asm volatile("wgmma.commit_group.sync.aligned;" ::: "memory"); }
template <int N> __device__ __forceinline__ void wg_wait() { asm volatile("wgmma.wait_group.sync.aligned %0;" ::"n"(N) : "memory"); }
template <int N> __device__ __forceinline__ void fence_regs(float (&a)[N]) {
#pragma unroll
  for (int i = 0; i < N; i++) asm volatile("" : "+f"(a[i])::"memory");
}
__device__ __forceinline__ uint32_t make_desc(uint32_t addr, uint32_t lbo) { return ((addr & 0x3FFFF) >> 4) | ((lbo >> 4) << 16); }
__device__ __forceinline__ void named_sync(int id, int n) { asm volatile("bar.sync %0, %1;" ::"r"(id), "r"(n) : "memory"); }
__device__ __forceinline__ uint32_t ld_relaxed(const void* p) { uint32_t v; asm volatile("ld.relaxed.gpu.global.u32 %0, [%1];" : "=r"(v) : "l"(p) : "memory"); return v; }
__device__ __forceinline__ uint32_t ld_relaxed_line(const void* p) { uint32_t v; asm volatile("ld.relaxed.gpu.global.L2::128B.u32 %0, [%1];" : "=r"(v) : "l"(p) : "memory"); return v; }
__device__ __forceinline__ void red_relaxed(uint32_t* p, uint32_t v) { asm volatile("red.relaxed.gpu.global.add.u32 [%0], %1;" ::"l"(p), "r"(v) : "memory"); }
__device__ __forceinline__ void st_relaxed(uint32_t* p, uint32_t v) { asm volatile("st.relaxed.gpu.global.u32 [%0], %1;" ::"l"(p), "r"(v) : "memory"); }
__device__ __forceinline__ uint2 ld_relaxed_b64(const uint2* p) {
  uint64_t a; asm volatile("ld.relaxed.gpu.global.b64 %0, [%1];" : "=l"(a) : "l"(p) : "memory");
  return make_uint2((uint32_t)a, (uint32_t)(a >> 32));
}
__device__ __forceinline__ void st_relaxed_b64(void* p, uint32_t lo, uint32_t hi) {
  uint64_t v = ((uint64_t)hi << 32) | lo;
  asm volatile("st.relaxed.gpu.global.b64 [%0], %1;" ::"l"(p), "l"(v) : "memory");
}
__device__ __forceinline__ void st_relaxed_v4(uint4* p, uint32_t a, uint32_t b, uint32_t c, uint32_t d) {
  asm volatile("st.relaxed.gpu.global.v4.u32 [%0], {%1,%2,%3,%4};" ::"l"(p), "r"(a), "r"(b), "r"(c), "r"(d) : "memory");
}
__device__ __forceinline__ bool empty(const uint4& v) { return v.x == ~0u || v.y == ~0u || v.z == ~0u || v.w == ~0u; }
__device__ __forceinline__ uint32_t tag_of(uint32_t ep) { return ep % 3 + 1; }
__device__ __forceinline__ uint32_t tagf(float v, uint32_t ep) {
  uint32_t r; asm volatile("lop3.b32 %0, %1, %2, 3, 0xD8;" : "=r"(r) : "r"(__float_as_uint(v)), "r"(ep)); return r;
}
__device__ __forceinline__ uint32_t tag_bad(const uint4& v, uint32_t ep) { return ((v.x ^ ep) | (v.y ^ ep) | (v.z ^ ep) | (v.w ^ ep)) & 3u; }
__device__ __forceinline__ uint4 ld_relaxed_v4(const void* p) {
  uint4 v; asm volatile("ld.relaxed.gpu.global.v4.u32 {%0,%1,%2,%3}, [%4];" : "=r"(v.x), "=r"(v.y), "=r"(v.z), "=r"(v.w) : "l"(p) : "memory"); return v;
}
__device__ __forceinline__ uint32_t ldg32(const void* p) { uint32_t v; asm volatile("ld.global.u32 %0, [%1];" : "=r"(v) : "l"(p) : "memory"); return v; }
__device__ __forceinline__ void stg128(uint4* p, uint32_t a, uint32_t b, uint32_t c, uint32_t d) {
  asm volatile("st.global.v4.b32 [%0], {%1,%2,%3,%4};" ::"l"(p), "r"(a), "r"(b), "r"(c), "r"(d) : "memory");
}
__device__ __forceinline__ void landed(uint32_t v) { if (__all_sync(~0u, v == 0xffffffffu)) __nanosleep(1); }
__device__ __forceinline__ void publish(uint32_t seen, uint32_t* cnt, uint32_t inc) {
  landed(seen);
  if (elect_one()) red_relaxed(cnt, inc);
}
__device__ __forceinline__ uint32_t pack_bf16(float lo, float hi) { uint32_t r; asm("cvt.rn.bf16x2.f32 %0, %1, %2;" : "=r"(r) : "f"(hi), "f"(lo)); return r; }
__device__ __forceinline__ float bf_lo(uint32_t v) { return __uint_as_float(v << 16); }
__device__ __forceinline__ float bf_hi(uint32_t v) { return __uint_as_float(v & 0xffff0000u); }
__device__ __forceinline__ uint32_t hmul2_bf16(uint32_t a, uint32_t b) { uint32_t r; asm("mul.rn.bf16x2 %0, %1, %2;" : "=r"(r) : "r"(a), "r"(b)); return r; }
__device__ __forceinline__ uint32_t hadd2_bf16(uint32_t a, uint32_t b) { uint32_t r; asm("add.rn.bf16x2 %0, %1, %2;" : "=r"(r) : "r"(a), "r"(b)); return r; }
__device__ __forceinline__ uint32_t hfma2_bf16(uint32_t a, uint32_t b, uint32_t c) { uint32_t r; asm("fma.rn.bf16x2 %0, %1, %2, %3;" : "=r"(r) : "r"(a), "r"(b), "r"(c)); return r; }
__device__ __forceinline__ void wgmma_n8(float (&d)[4], uint32_t descA, uint32_t descB, int scaleD) {
  asm volatile("{\n.reg .pred p;\n.reg .b64 da, db;\nmov.b64 da, {%4, 0x40000040};\nmov.b64 db, {%5, 0x40000040};\nsetp.ne.b32 p, %6, 0;\n"
               "wgmma.mma_async.sync.aligned.m64n8k16.f32.bf16.bf16 {%0,%1,%2,%3}, da, db, p, 1, 1, 1, 0;\n}\n"
               : "+f"(d[0]), "+f"(d[1]), "+f"(d[2]), "+f"(d[3]) : "r"(descA), "r"(descB), "r"(scaleD));
}
__device__ __forceinline__ float ex2(float x) { float r; asm("ex2.approx.ftz.f32 %0, %1;" : "=f"(r) : "f"(x)); return r; }
__device__ __forceinline__ float rcp(float x) { float r; asm("rcp.approx.ftz.f32 %0, %1;" : "=f"(r) : "f"(x)); return r; }
__device__ __forceinline__ float silu_f(float x) { return x * rcp(1.f + ex2(x * -1.4426950408889634f)); }
__device__ __forceinline__ float swiglu(float h, float hu) {
  float t; asm("tanh.approx.f32 %0, %1;" : "=f"(t) : "f"(h));
  return fmaf(hu, t, hu);
}
__device__ __forceinline__ void ldsm4(uint32_t addr, uint32_t& a, uint32_t& b, uint32_t& c, uint32_t& d) {
  asm volatile("ldmatrix.sync.aligned.m8n8.x4.shared.b16 {%0,%1,%2,%3}, [%4];" : "=r"(a), "=r"(b), "=r"(c), "=r"(d) : "r"(addr) : "memory");
}
__device__ __forceinline__ void stsm4(uint32_t addr, uint32_t a, uint32_t b, uint32_t c, uint32_t d) {
  asm volatile("stmatrix.sync.aligned.m8n8.x4.shared.b16 [%0], {%1,%2,%3,%4};" ::"r"(addr), "r"(a), "r"(b), "r"(c), "r"(d) : "memory");
}
__device__ __forceinline__ void sts128(uint32_t addr, uint32_t a, uint32_t b, uint32_t c, uint32_t d) {
  asm volatile("st.shared.v4.b32 [%0], {%1,%2,%3,%4};" ::"r"(addr), "r"(a), "r"(b), "r"(c), "r"(d) : "memory");
}
__device__ __forceinline__ void sts64(uint32_t addr, uint32_t a, uint32_t b) { asm volatile("st.shared.v2.b32 [%0], {%1,%2};" ::"r"(addr), "r"(a), "r"(b) : "memory"); }
__device__ __forceinline__ void sts32(uint32_t addr, uint32_t a) { asm volatile("st.shared.b32 [%0], %1;" ::"r"(addr), "r"(a) : "memory"); }
__device__ __forceinline__ uint4 lds128(uint32_t addr) {
  uint4 v; asm volatile("ld.shared.v4.b32 {%0,%1,%2,%3}, [%4];" : "=r"(v.x), "=r"(v.y), "=r"(v.z), "=r"(v.w) : "r"(addr) : "memory"); return v;
}
__device__ __forceinline__ uint32_t lds32(uint32_t addr) { uint32_t v; asm volatile("ld.shared.b32 %0, [%1];" : "=r"(v) : "r"(addr) : "memory"); return v; }
__device__ __forceinline__ uint32_t movm(uint32_t a) { uint32_t d; asm volatile("movmatrix.sync.aligned.m8n8.trans.b16 %0, %1;" : "=r"(d) : "r"(a)); return d; }
__device__ __forceinline__ void mma16816(float (&c)[4], uint32_t a0, uint32_t a1, uint32_t a2, uint32_t a3, uint32_t b0, uint32_t b1) {
  asm volatile("mma.sync.aligned.m16n8k16.row.col.f32.bf16.bf16.f32 {%0,%1,%2,%3},{%4,%5,%6,%7},{%8,%9},{%0,%1,%2,%3};"
               : "+f"(c[0]), "+f"(c[1]), "+f"(c[2]), "+f"(c[3]) : "r"(a0), "r"(a1), "r"(a2), "r"(a3), "r"(b0), "r"(b1));
}
__device__ __forceinline__ void mma16816z(float (&c)[4], uint32_t a0, uint32_t a1, uint32_t a2, uint32_t a3, uint32_t b0, uint32_t b1) {
  asm volatile("mma.sync.aligned.m16n8k16.row.col.f32.bf16.bf16.f32 {%0,%1,%2,%3},{%4,%5,%6,%7},{%8,%9},{%10,%10,%10,%10};"
               : "=f"(c[0]), "=f"(c[1]), "=f"(c[2]), "=f"(c[3]) : "r"(a0), "r"(a1), "r"(a2), "r"(a3), "r"(b0), "r"(b1), "f"(0.f));
}
__device__ __forceinline__ void mma1688(float (&c)[4], uint32_t a0, uint32_t a1, uint32_t b0) {
  asm volatile("mma.sync.aligned.m16n8k8.row.col.f32.bf16.bf16.f32 {%0,%1,%2,%3},{%4,%5},{%6},{%0,%1,%2,%3};"
               : "+f"(c[0]), "+f"(c[1]), "+f"(c[2]), "+f"(c[3]) : "r"(a0), "r"(a1), "r"(b0));
}
__device__ __forceinline__ float quad_max(float v) { v = fmaxf(v, __shfl_xor_sync(~0u, v, 1)); return fmaxf(v, __shfl_xor_sync(~0u, v, 2)); }
__device__ __forceinline__ float quad_sum(float v) { v += __shfl_xor_sync(~0u, v, 1); return v + __shfl_xor_sync(~0u, v, 2); }
__device__ __forceinline__ uint32_t opaque(uint32_t v) { asm volatile("" : "+r"(v)); return v; }
__device__ __forceinline__ uint32_t tid_now() { uint32_t v; asm volatile("mov.u32 %0, %%tid.x;" : "=r"(v)); return v; }
__device__ __forceinline__ void arrive_after(uint32_t bar, float v) {
  asm volatile("{\n.reg .pred p, q;\n.reg .b32 c;\nmov.b32 c, %1;\nelect.sync _|q, 0xffffffff;\n"
               "L: @q mbarrier.arrive.shared::cta.b64 _, [%0];\nsetp.eq.u32 p, c, 0x7fedcba9;\nadd.u32 c, c, 1;\nsetp.ne.u32 q, c, c;\n@p bra L;\n}"
               ::"r"(bar), "r"(__float_as_uint(v)) : "memory");
}
__device__ __forceinline__ int since(int t0) { return (int)((uint32_t)clock() - (uint32_t)t0); }
__device__ __forceinline__ void until(int t0, uint32_t t) { while ((uint32_t)since(t0) < t) {} }
__device__ __forceinline__ void in_order() { const int t = (int)clock(); while (since(t) < 0) {} }
__device__ __forceinline__ void spin(int clocks) { until((int)clock(), clocks); }

constexpr float ATT_SCALE_LOG2E = 0.17677669529663687f * 1.4426950408889634f;

constexpr int T_XA = 2600;
constexpr int P_XB = 100;
constexpr int P_ACT = 140;
constexpr int T_Q2 = 4200;
constexpr int T_Q3 = 4600;
constexpr int T_XB = 8200;
constexpr int DELAY_ST = 150;
constexpr int T_W0 = 3200;
constexpr int T_G0 = 4500;
constexpr int T_G1 = 7400;
constexpr int P_G2 = 690;
constexpr int P_G2B = 820;
constexpr int F_G2A = 700;
constexpr int F_G2B = 750;
constexpr int P_Q = 240;
constexpr int T_W = 5500;
constexpr int P_W = 1200;
constexpr int DELAY_HELP = 3000;

struct Pipe {
  const uint2* tab;
  uint32_t bars, peer_bars;
  uint2 nx;
  uint32_t prev;
  bool ready;
  bool lead;
  __device__ __forceinline__ uint2 begin(int n) {
    const uint2 e = nx;
    nx = tab[n + 1];
    if (!ready) {
      mbar_wait(bars + (e.y & 0x3ff), (e.y >> 10) & 1);
      mbar_wait(bars + ((e.y >> 16) & 0x7ff), e.y >> 31);
    }
    ready = false;
    return e;
  }
  __device__ __forceinline__ void release_now(uint32_t y) {
    asm volatile("{\n.reg .pred p, q;\n.reg .b32 c;\nmov.b32 c, %2;\nelect.sync _|q, 0xffffffff;\nsetp.ne.and.u32 q, c, 0, q;\n"
                 "L: @q mbarrier.arrive.shared::cta.b64 _, [%0];\n@q mbarrier.arrive.shared::cluster.b64 _, [%1];\n"
                 "setp.eq.u32 p, c, 1;\nadd.u32 c, c, 1;\n@p bra L;\n}"
                 ::"r"(bars + 512 + (y & 0x3ff)), "r"(peer_bars + 512 + (y & 0x3ff)), "r"(opaque(lead ? y & 0x800 : 0)) : "memory");
  }
  template <bool PAUSES = false> __device__ __forceinline__ void end(uint32_t y) {
    const bool r0 = mbar_test(bars + (nx.y & 0x3ff), (nx.y >> 10) & 1), r1 = mbar_test(bars + ((nx.y >> 16) & 0x7ff), nx.y >> 31);
    wg_wait<1>();
    release(prev);
    prev = y;
    if (PAUSES && (y & 0x1000)) { wg_wait<0>(); release(y); prev = 0; }
    ready = __all_sync(~0u, r0 && r1);
  }
  __device__ __forceinline__ void release(uint32_t y) {
    if (lead && (y & 0x800)) { if (elect_one()) { mbar_arrive(bars + 512 + (y & 0x3ff)); mbar_arrive_remote(peer_bars + 512 + (y & 0x3ff)); } }
  }
};
__device__ __forceinline__ constexpr uint32_t qa(int q) { return (q >> 1) * 256 + (q & 1) * 2; }

__device__ __forceinline__ uint32_t img_pos(uint32_t w, uint32_t lane) { return (w * 16 + (lane >> 2)) * 4 + ((lane & 3) ^ (lane >> 3)); }
__device__ __forceinline__ uint32_t img_line(uint32_t w, uint32_t lane) { return (lane >> 3) * 256 + w * 64 + (lane & 7) * 8; }

template <int MULTICAST>
__device__ __forceinline__ void tiles(uint32_t bars, const uint2* tab, uint2& nx, int n0, int n1, uint32_t dst, const char* src, uint32_t bytes,
                                      const uint32_t* cnt, uint32_t target, int pace, int head) {
  int due = 0;
#pragma unroll 1
  for (int n = n0; n < n1; n++) {
    const uint2 e = nx;
    nx = tab[n + 1];
    const uint32_t fb = bars + (e.y & 0x3ff);
    mbar_expect_tx(fb, (e.y >> 29) << 13);
    if (e.x & 0x1000000) {
      while ((int32_t)(ld_relaxed_line(cnt + ((e.x >> 25) & 31)) - target) < 0) {}
      asm volatile("fence.acquire.gpu;" ::: "memory"); fence_async_glob();
      if (!MULTICAST) due = since(head);
    }
    mbar_wait(bars + (e.x & 0x7ff), e.x >> 31);
    if (MULTICAST) bulk_g2s_mc(dst + (e.y & 0x3c000), src + (e.x & 0x3fc000), bytes, fb);
    else {
      until(due, (n - n0) * pace);
      bulk_g2s(dst + (e.y & 0x3c000), src + (e.x & 0x3fc000), bytes, fb);
    }
  }
}

template <int BOXES>
__device__ __forceinline__ void weights(uint32_t sb, uint2& nx, int& n, const CUtensorMap* m0, const CUtensorMap* m1, const CUtensorMap* m2, int c0, int c1, int c2, int dk) {
  const uint32_t bars = sb + BAR_OFF;
#pragma unroll 1
  for (bool more = true; more; n++) {
    const uint2 e = nx;
    nx = c_w[0][n + 1];
    more = !(e.y & 0x20000);
    const uint32_t fb = bars + (e.y & 0x3ff), dst = sb + W_OFF + (e.y & 0x1e000);
    const int k0 = (e.y >> 24) + dk;
    if (e.x & 0x7ff) mbar_wait(bars + (e.x & 0x7ff), (e.x >> 15) & 1);
    mbar_wait(bars + ((e.x >> 16) & 0x7ff), e.x >> 31);
    if (BOXES == 2) { tma5d_once(dst, m0, fb, c0, k0); tma5d_once(dst + 8192, m1, fb, c1, k0); }
    else { tma5d(dst, m0, fb, c0, k0); tma5d(dst + 8192, m1, fb, c1, k0); tma5d(dst + 16384, m2, fb, c2, k0); }
  }
}

__device__ __forceinline__ void mod_slice(uint32_t sb, uint32_t* dst, uint32_t tag, uint32_t w, uint32_t lane) {
  float e[4];
#pragma unroll 1
  for (int kb = 0; kb < 4; kb++) {
    mbar_wait(sb + BAR_OFF + B_SL + 8 * kb, 0);
    wg_fence();
#pragma unroll
    for (int q = 0; q < 4; q++) wgmma_n8(e, make_desc(SMEM_BASE + SL_OFF + kb * 8192, 8192) + q * 128, make_desc(SMEM_BASE + TAB_OFF + 4096 + kb * 256, 16) + q * 2, kb | q);
    wg_commit();
  }
  wg_wait<0>();
  fence_regs(e);
  if ((lane & 3) == 0) { st_relaxed(dst + w * 16 + (lane >> 2), tagf(e[0], tag)); st_relaxed(dst + w * 16 + 8 + (lane >> 2), tagf(e[2], tag)); }
  if (w == 0 && lane == 0) mbar_arrive(sb + BAR_OFF + B_SLE);
  __syncwarp();
}

__device__ __forceinline__ int mod_group(int job, int hc) { return (job >> 1) * 16 + hc * 4 + (job & 1) * 2; }

template <bool BY_SM>
__global__ void __cluster_dims__(2, 1, 1) __launch_bounds__(NTHREADS, 1) fused_kernel(const Ptrs Q, const __grid_constant__ Params P) {
  extern __shared__ __align__(1024) uint8_t smem_raw[];
  const int t0 = (int)clock();
  int cta = blockIdx.x;
  {
    uint32_t smid;
    asm volatile("mov.u32 %0, %%smid;" : "=r"(smid));
    const int tp = smid >> 1;
    const int cl = tp < 32 ? tp : (tp < 60 ? tp + 1 + (tp - 32) / 7 : (tp < 62 ? tp + 4 : (tp - 58) * 8));
    if (BY_SM) cta = cl * 2 + (cta & 1);
    cta = __shfl_sync(~0u, cta, 0);
  }
  const int grp = cta >> 4, j = cta & 15, rank = cta & 1, typ = j >> 3;
  const int wg = __shfl_sync(~0u, (int)threadIdx.x >> 7, 0);
  const int warp = __shfl_sync(~0u, (int)threadIdx.x >> 5, 0);
  const uint32_t sb = mapa(SMEM_BASE, rank), bars = sb + BAR_OFF;
  if (warp == 10 && cta < NCTA && elect_one()) {
    prefetch_tmap(&P.mWm2);
#pragma unroll
    for (int i = 0; i < 4; i++) mbar_init(bars + B_SL + 8 * i, 1);
    fence_async_smem();
    if (cta < 64) {
#pragma unroll
      for (int i = 0; i < 4; i++) {
        mbar_expect_tx(bars + B_SL + 8 * i, 8192);
        tma2d_once(sb + SL_OFF + i * 8192, &P.mWm2, bars + B_SL + 8 * i, ((cta >> 4) & 1) * D_ + (cta >> 5) * 256 + ((cta >> 2) & 3) * 64, (cta & 3) * 256 + i * 64);
      }
    }
  }
  __syncwarp();

  if (cta >= NCTA) {
    const uint32_t lane = tid_now() & 31, cf = sb + 196608, hb = cf + 16384;
    const int hc = cta - NCTA;
    if (threadIdx.x == 0) {
#pragma unroll 1
      for (int i = 0; i < 48; i++) mbar_init(hb + 8 * i, 1);
#pragma unroll 1
      for (int i = 0; i < 24; i++) mbar_init(bars + 8 * i, (i >> 1) == 6 ? 4 : 1);
    }
    const uint32_t ep = ld_relaxed(&Q.s->ep[cta * 32 + lane]) + 1;
#pragma unroll 1
    for (int kb = warp; kb < 16; kb += 12) {
      const uint32_t cv = ((const uint32_t*)Q.c)[kb * 32 + lane];
      sts32(cf + kb * 256 + (lane & 3) * 4 + (((lane >> 2) ^ ((2 * kb) & 7)) << 4), pack_bf16(silu_f(bf_lo(cv)), silu_f(bf_hi(cv))));
    }
    fence_async_smem();
    __syncthreads();
    if (wg == 2) {
      if (elect_one()) {
        spin(DELAY_HELP);
        uint32_t s = warp & 3, ph = 1;
#pragma unroll 1
        for (int n = (warp >> 1) & 1; n < 8 * 16; n += 2) {
          mbar_wait(hb + 8 * (24 + s), ph);
          mbar_expect_tx(hb + 8 * s, 8192);
          tma2d_once(sb + s * 8192, &P.mWm2, hb + 8 * s, (32 + mod_group(n >> 4, hc) + (warp & 1)) * 64, (n & 15) * 64);
          s += 4; if (s >= 24) { s -= 24; ph ^= 1; }
        }
      }
      __syncwarp();
      if (warp == 8) Q.s->ep[cta * 32 + lane] = ep;
    } else {
      uint32_t s = wg, ph = 0;
#pragma unroll 1
      for (int job = 0; job < 8; job++) {
        float e[4];
#pragma unroll 1
        for (int kb = 0; kb < 16; kb += 4) {
#pragma unroll 1
          for (int i = 0; i < 4; i++) {
            mbar_wait(hb + 8 * (s + 2 * i), ph);
            wg_fence();
#pragma unroll
            for (int q = 0; q < 4; q++)
              wgmma_n8(e, make_desc(SMEM_BASE, 8192) + (s + 2 * i) * 512 + q * 128, make_desc(SMEM_BASE + 196608, 16) + (kb + i) * 16 + q * 2, kb | i | q);
            wg_commit();
          }
          wg_wait<0>();
          if ((warp & 3) == 0 && elect_one()) {
#pragma unroll
            for (int i = 0; i < 4; i++) mbar_arrive(hb + 8 * (24 + s + 2 * i));
          }
          s += 8; if (s >= 24) { s -= 24; ph ^= 1; }
        }
        fence_regs(e);
        if ((lane & 3) == 0) {
          uint32_t* dst = Q.s->modp + (mod_group(job, hc) + wg) * 64 + (warp & 3) * 16 + (lane >> 2);
          st_relaxed(dst, tagf(e[0], tag_of(ep))); st_relaxed(dst + 8, tagf(e[2], tag_of(ep)));
          const uint32_t g = pack_bf16(2.f * __uint_as_float(tagf(e[0], tag_of(ep))), 2.f * __uint_as_float(tagf(e[2], tag_of(ep))));
          const uint32_t a = sb + PAR_OFF + ((job & 1) * 4 + wg * 2 + ((warp >> 1) & 1)) * 64 + (lane >> 3) * 16 + (warp & 1) * 8 + ((lane >> 2) & 1) * 2;
          asm volatile("st.shared.u16 [%0], %1;\nst.shared.u16 [%0 + 4], %2;" ::"r"(a), "h"((uint16_t)g), "h"((uint16_t)(g >> 16)) : "memory");
        }
        __syncwarp();
      }
    }
    __syncthreads();
    if (warp == 8) {
      if (only_one()) {
        mbar_expect_tx(bars + 64, N_HK * 32768);
#pragma unroll 1
        for (int i = 0; i < 4 * N_HK; i++) tma5d(sb + i * 8192, &P.mWd, bars + 64, hc * 256 + (i & 3) * 64, (i >> 2) * 2);
        uint32_t n = 0;
#pragma unroll 1
        for (int rb = 0; rb < 16; rb++) {
          while ((int32_t)(ld_relaxed(Q.s->cnt + (rb & 7) * 32 + (rb < 8 ? G_HK : 8 + G_ACT)) - (rb < 8 ? 4 * N_HK : 64) * ep) < 0) __nanosleep(50);
          asm volatile("fence.acquire.gpu;" ::: "memory"); fence_async_glob();
#pragma unroll 1
          for (int i = 0; i < 2 * N_HK; i++, n++) {
            mbar_wait(bars + 128 + 8 * (n & 7), ((n >> 3) & 1) ^ 1);
            mbar_expect_tx(bars + 8 * (n & 7), 8192);
            bulk_g2s(sb + 98304 + (n & 7) * 8192, Q.s->img + (size_t)((rb & 7) * N_TILES + T_ACT + (rb >> 3) * 56 + i % N_HK) * 1024 + i / N_HK * 512, 8192, bars + 8 * (n & 7));
          }
        }
      }
    } else if (warp >= 10) {
      if (only_one()) {
        const int q = warp & 1;
#pragma unroll 1
        for (int rb = 0; rb < 16; rb++) {
          mbar_wait(bars + 96 + 8 * q, rb & 1);
#pragma unroll 1
          for (int i = 0; i < 8; i++)
            asm volatile("cp.reduce.async.bulk.global.shared::cta.bulk_group.add.noftz.bf16 [%0], [%1], 4096;"
                         ::"l"(Q.s->img + (size_t)((rb & 7) * N_TILES + T_X1 + (rb >> 3) * 16 + hc * 4 + (i >> 1)) * 1024 + q * 512 + (i & 1) * 256), "r"(sb + 163840 + q * 32768 + i * 4096) : "memory");
          bulk_commit();
          bulk_wait_read();
          mbar_arrive(bars + 80 + 8 * q);
        }
        asm volatile("cp.async.bulk.wait_group 0;" ::: "memory");
        fence_async_glob(); asm volatile("fence.acq_rel.gpu;" ::: "memory");
#pragma unroll 1
        for (int i = 0; i < 8; i++) red_relaxed(Q.s->cnt + i * 32 + G_X1, 8);
      }
    } else if (wg < 2) {
      const uint32_t w = warp & 3;
      uint32_t n = wg * N_HK;
      mbar_wait(bars + 64, 0);
#pragma unroll 1
      for (int rb = 0; rb < 16; rb++) {
        float acc[128];
        mbar_wait(bars + 112 + 8 * wg, (rb & 1) ^ wg ^ 1);
#pragma unroll 1
        for (int kb = 0; kb < N_HK; kb++, n++) {
          mbar_wait(bars + 8 * (n & 7), (n >> 3) & 1);
          const uint32_t da = make_desc(SMEM_BASE + 98304, 16) + (n & 7) * 512, db = make_desc(SMEM_BASE, 8192) + kb * 2048;
          wg_fence();
#pragma unroll
          for (int q = 0; q < 4; q++) wg_n256<H64, H128>(acc, da + qa(q), db + 128 * q, q ? 1 : kb);
          wg_commit();
          wg_wait<1>();
          if (kb && w == 0 && elect_one()) mbar_arrive(bars + 128 + 8 * ((n - 1) & 7));
        }
        if (w == 0 && elect_one()) mbar_arrive(bars + 120 - 8 * wg);
        wg_wait<0>();
        if (w == 0 && elect_one()) mbar_arrive(bars + 128 + 8 * ((n - 1) & 7));
        mbar_wait(bars + 80 + 8 * wg, (rb & 1) ^ 1);
        fence_regs(acc);
        const uint32_t ln = tid_now() & 31, st = sb + 163840 + wg * 32768 + img_pos(w, ln) * 16;
        uint4 gn = lds128(sb + PAR_OFF + (ln & 3) * 16);
#pragma unroll
        for (int c = 0; c < 8; c++) {
          const uint4 g = gn;
          if (c < 7) gn = lds128(sb + PAR_OFF + (c + 1) * 64 + (ln & 3) * 16);
#pragma unroll
          for (int f = 0; f < 2; f++) {
            const float* a = &acc[16 * c + 2 * f];
            sts128(st + c * 4096 + f * 512, hmul2_bf16(g.x, pack_bf16(a[0], a[1])), hmul2_bf16(g.y, pack_bf16(a[4], a[5])),
                   hmul2_bf16(g.z, pack_bf16(a[8], a[9])), hmul2_bf16(g.w, pack_bf16(a[12], a[13])));
          }
        }
        n += N_HK;
        fence_async_smem(); __syncwarp();
        if (elect_one()) mbar_arrive(bars + 96 + 8 * wg);
      }
    }
  } else if (wg < 2) {
    asm volatile("setmaxnreg.inc.sync.aligned.u32 232;");
    const int w = warp & 3, rb = wg * 8 + grp;
    uint4* const img = Q.s->img + (size_t)grp * (N_TILES * 1024);
    uint32_t* const cnt = Q.s->cnt + grp * 32 + wg * 8;
    {
      const uint32_t tid = tid_now() & 127, lane = tid & 31;
      const uint32_t row = 8 * j + 2 * w + (lane >> 4);
      if (tid < 64) st_relaxed_b64(Q.s->stat + ((rb * 2 + rank) * 8 + (j >> 1)) * 64 + tid, 0, 0);
      uint4* dst = img + (T_H + wg * 16 + ((lane >> 3) & 1)) * 1024 + row * 8 + ((lane ^ row) & 7);
      const uint4* back = img + (T_H + wg * 16 + (lane >> 1)) * 1024 + (8 * j + 2 * w + (lane & 1)) * 8;
      const uint32_t tab = sb + TAB_OFF + (lane & 15) * 16;
      if (wg) {
        const uint32_t ep0 = ld_relaxed(&Q.s->ep[cta * 32 + lane]);
        uint32_t* mdst = Q.s->mod0 + ((cta >> 5) * 4 + (cta & 3)) * 512 + ((cta >> 2) & 7) * 64;
        const uint32_t cv = ldg32(Q.c + (cta & 3) * 256 + tid * 2);
        if (tid < 64) st_relaxed(mdst + tid, 0);
        uint4* mbox = Q.s->halo + (size_t)(grp * 16 + j) * 128 + tid;
        st_relaxed_v4(mbox, ~0u, ~0u, ~0u, ~0u); st_relaxed_v4(mbox + 128 * 128, ~0u, ~0u, ~0u, ~0u);
        const uint32_t s0 = ld_relaxed(mbox), s1 = ld_relaxed(mbox + 128 * 128);
        named_sync(0, NTHREADS);
        asm volatile("barrier.cluster.arrive.relaxed.aligned;" ::: "memory");
        in_order();
        sts32(sb + TAB_OFF + 4096 + w * 256 + (lane & 3) * 4 + (((lane >> 2) ^ (2 * w)) << 4), pack_bf16(silu_f(bf_lo(opaque(cv))), silu_f(bf_hi(cv))));
        fence_async_smem();
        if (__any_sync(~0u, (opaque(s0) & opaque(s1)) == 0)) __nanosleep(1);
        named_sync(2, 128);
        asm volatile("barrier.cluster.wait.aligned;" ::: "memory");
        const uint32_t ep = tag_of(opaque(ep0) + 1);
        uint4 xa[4];
#pragma unroll
        for (int i = 0; i < 4; i++) xa[i] = make_uint4(0, 0, 0, 0);
#pragma unroll 1
        for (int s = 0; s < 2; s++) {
          if ((cta >> 6) == s) mod_slice(sb, mdst, ep, w, lane);
          until(t0, s ? T_G1 : T_G0);
          const uint4* ms = (const uint4*)Q.s->mod0 + (2 * s + rank) * 512 + tid;
          uint4 p[4];
#pragma unroll
          for (int i = 0; i < 4; i++) p[i] = make_uint4(0, 0, 0, 0);
          uint32_t it = 0;
          do {
#pragma unroll
            for (int i = 0; i < 4; i++) if (tag_bad(p[i], ep)) p[i] = ld_relaxed_v4(ms + i * 128);
          } while (__any_sync(~0u, tag_bad(p[0], ep) | tag_bad(p[1], ep) | tag_bad(p[2], ep) | tag_bad(p[3], ep)) && ++it < POLL_MAX);
#define F4(f) ((__uint_as_float(p[0].f) + __uint_as_float(p[1].f)) + (__uint_as_float(p[2].f) + __uint_as_float(p[3].f)))
          uint32_t c0 = pack_bf16(F4(x), F4(y)), c1 = pack_bf16(F4(z), F4(w));
#undef F4
          if (w >= 2) { c0 = hadd2_bf16(c0, 0x3f803f80u); c1 = hadd2_bf16(c1, 0x3f803f80u); }
          const uint32_t ta = TAB_OFF + (tid >> 6) * 2048 + (2 * s + rank) * 512 + (tid & 63) * 8, peer = mapa(SMEM_BASE, rank ^ 1);
          asm volatile("st.async.weak.shared::cluster.mbarrier::complete_tx::bytes.v2.b32 [%0], {%2,%3}, [%1];" ::"r"(peer + ta), "r"(peer + BAR_OFF + B_ST + 8 * s), "r"(c0), "r"(c1) : "memory");
          sts64(sb + ta, c0, c1);
          if (s == 0) {
            mbar_wait(bars + B_XB, 0);
#pragma unroll
            for (int i = 0; i < 4; i++) xa[i] = lds128(sb + 4 * 16384 + (row & 7) * 2048 + 1024 + i * 256 + (lane & 15) * 16);
            landed(xa[0].x & xa[1].x & xa[2].x & xa[3].x);
          }
          __syncwarp();
          if (elect_one()) mbar_expect_tx(bars + B_ST + 8 * s, 256);
        }
        mbar_wait(bars + B_ST + 8, 0);
        const float m = __uint_as_float(lds32(sb + TAB_OFF + 6144 + tid * 8)), v = __uint_as_float(lds32(sb + TAB_OFF + 6148 + tid * 8));
#pragma unroll
        for (int i = 4; i < 8; i++) {
          const uint4 a = lds128(tab + i * 256), c = lds128(tab + 2048 + i * 256);
#define NRM(x) pack_bf16(fmaf(bf_lo(x), v, m), fmaf(bf_hi(x), v, m))
          stg128(dst - 16384 + i * 2048, hfma2_bf16(NRM(xa[i & 3].x), c.x, a.x), hfma2_bf16(NRM(xa[i & 3].y), c.y, a.y),
                 hfma2_bf16(NRM(xa[i & 3].z), c.z, a.z), hfma2_bf16(NRM(xa[i & 3].w), c.w, a.w));
#undef NRM
        }
        publish(lane >= 16 ? ld_relaxed(back - 16384) : 0, cnt - 8 + G_H1, 1);
      } else {
        named_sync(0, NTHREADS);
        asm volatile("barrier.cluster.arrive.relaxed.aligned;\nbarrier.cluster.wait.aligned;" ::: "memory");
      }
      mbar_wait(bars + B_XB + 8 * wg, 0);
      float d[64], m = 0.f, v = 0.f, m2 = 0.f, v2 = 0.f;
#pragma unroll
      for (int i = 0; i < 8; i++) {
        const uint4 t = lds128(sb + (4 + wg) * 16384 + (row & 7) * 2048 + i * 256 + (lane & 15) * 16);
        const uint32_t x[4] = {t.x, t.y, t.z, t.w};
#pragma unroll
        for (int e = 0; e < 4; e++) {
          const float d0 = bf_lo(x[e]), d1 = bf_hi(x[e]);
          d[8 * i + 2 * e] = d0; d[8 * i + 2 * e + 1] = d1;
          m += d0; m2 += d1; v = fmaf(d0, d0, v); v2 = fmaf(d1, d1, v2);
        }
      }
      m += m2; v += v2;
#pragma unroll
      for (int i = 1; i < 16; i *= 2) { m += __shfl_xor_sync(~0u, m, i); v += __shfl_xor_sync(~0u, v, i); }
      m *= 1.f / D_;
      v = rsqrtf(fmaxf(fmaf(-m, m, v * (1.f / D_)), 0.f) + 1e-5f);
      m = -m * v;
      if (!wg) {
        sts64(sb + TAB_OFF + 6144 + tid * 8, __float_as_uint(m), __float_as_uint(v));
        __syncwarp();
        if (elect_one()) mbar_arrive(bars + B_ST + 8);
      }
      mbar_wait(bars + B_ST, 0);
#pragma unroll
      for (int s = 0; s < 2; s++) {
        if (s > wg) break;
#pragma unroll
        for (int i = 4 * s; i < 4 * s + 4; i++) {
          const uint4 a = lds128(tab + i * 256), c = lds128(tab + 2048 + i * 256);
#define NRM(e) pack_bf16(fmaf(d[8 * i + 2 * e], v, m), fmaf(d[8 * i + 2 * e + 1], v, m))
          stg128(dst + i * 2048, hfma2_bf16(NRM(0), c.x, a.x), hfma2_bf16(NRM(1), c.y, a.y), hfma2_bf16(NRM(2), c.z, a.z), hfma2_bf16(NRM(3), c.w, a.w));
#undef NRM
        }
      }
      publish(wg || lane < 16 ? ld_relaxed(back) : 0, cnt + G_H0, 1);
    }

    Pipe pp;
    pp.tab = c_cons[wg];
    pp.bars = bars; pp.peer_bars = mapa(bars, rank ^ 1); pp.lead = w == 0; pp.prev = 0; pp.ready = false;
    pp.nx = pp.tab[0];
    const uint32_t dA0 = make_desc(SMEM_BASE, 16), dB0 = make_desc(SMEM_BASE + W_OFF, 8192);
    const uint32_t dAo = dA0 + rank * 512, dAp = dA0 + 512 - rank * 512;

    {
      float acc[2][96];
#pragma unroll 1
      for (int n = 0; n < 14; n++) {
        const uint2 e = pp.begin(n);
        const uint32_t da = dA0 + (e.x & 0xffff), db = dB0 + (e.x >> 16);
        wg_fence();
#pragma unroll
        for (int q = 0; q < 4; q++) {
          wg_n192<H128, H128>(acc[0], da + 2 * q, db + 128 * q, q ? 1 : n);
          wg_n192<H128, H128>(acc[1], da + 2 * q + 512, db + 128 * q, q ? 1 : n);
        }
        wg_commit();
        pp.template end<true>(e.y);
      }
      const uint2 e0 = pp.begin(14), e1 = pp.begin(15);
#pragma unroll
      for (int h = 1; h >= 0; h--) {
        wg_fence();
#pragma unroll
        for (int q = 0; q < 4; q++) wg_n192<H128, H128>(acc[h], dA0 + (e0.x & 0xffff) + 2 * q + 512 * h, dB0 + (e0.x >> 16) + 128 * q, 1);
#pragma unroll
        for (int q = 0; q < 4; q++) wg_n192<H128, H128>(acc[h], dA0 + (e1.x & 0xffff) + 2 * q + 512 * h, dB0 + (e1.x >> 16) + 128 * q, 1);
        wg_commit();
        if (h) { wg_wait<1>(); pp.release(pp.prev); }
      }
      if (pp.lead && elect_one()) mbar_arrive(bars + B_Q + 8 * wg);
      const uint2 ea = pp.begin(16);
      const uint32_t lane = tid_now() & 31, g = lane >> 2, t = lane & 3;
      const uint32_t hal = sb + (ea.x & 0xffff) * 16 + w * 2048 + lane * 16;
      uint4* mbox = Q.s->halo + (size_t)(rb * 16 + j) * 128 + lane;
      const bool first = w == 0 && grp == 0;
      uint32_t qp[2][8][2], kp[2][8][2], vp[2][8][2];
      uint4 hk[2][2], hw[2][2];
#pragma unroll
      for (int h = 1; h >= 0; h--) {
        if (h) wg_wait<1>(); else { in_order(); wg_wait<0>(); pp.release(e0.y); pp.release_now(e1.y); }
        fence_regs(acc[h]);
#pragma unroll
        for (int i = 0; i < 8; i++) {
          kp[h][i][1] = pack_bf16(acc[h][32 + 4 * i + 2], acc[h][32 + 4 * i + 3]);
          vp[h][i][1] = pack_bf16(acc[h][64 + 4 * i + 2], acc[h][64 + 4 * i + 3]);
        }
        if (h == 1 && w == 3 && grp < 7) {
#pragma unroll
          for (int d = 0; d < 2; d++) {
            st_relaxed_v4(mbox + 16 * 128 + d * 32, kp[h][4 * d][1], kp[h][4 * d + 1][1], kp[h][4 * d + 2][1], kp[h][4 * d + 3][1]);
            st_relaxed_v4(mbox + 16 * 128 + d * 32 + 64, vp[h][4 * d][1], vp[h][4 * d + 1][1], vp[h][4 * d + 2][1], vp[h][4 * d + 3][1]);
          }
        }
        if (h == 0) {
#pragma unroll
          for (int d = 0; d < 2; d++) {
            hk[0][d] = hw[0][d] = make_uint4(0, 0, 0, 0);
            if (w == 0) { hk[0][d] = ld_relaxed_v4(mbox + d * 32); hw[0][d] = ld_relaxed_v4(mbox + d * 32 + 64); }
          }
        }
#pragma unroll
        for (int i = 0; i < 8; i++) vp[h][i][1] = movm(vp[h][i][1]);
        if (h == 0 || w < 3) {
#pragma unroll
          for (int d = 0; d < 2; d++) {
            sts128(hal + 2048 + h * 8192 + d * 1024, kp[h][4 * d][1], kp[h][4 * d + 1][1], kp[h][4 * d + 2][1], kp[h][4 * d + 3][1]);
            sts128(hal + 2048 + h * 8192 + d * 1024 + 512, vp[h][4 * d][1], vp[h][4 * d + 1][1], vp[h][4 * d + 2][1], vp[h][4 * d + 3][1]);
          }
        }
        if (h == 0) {
          named_sync(1 + wg, 128);
#pragma unroll
          for (int d = 0; d < 2; d++) {
            if (w) { hk[0][d] = lds128(hal + d * 1024); hw[0][d] = lds128(hal + d * 1024 + 512); }
            hk[1][d] = lds128(hal + 8192 + d * 1024); hw[1][d] = lds128(hal + 8192 + d * 1024 + 512);
          }
        }
#pragma unroll
        for (int i = 0; i < 8; i++) {
          kp[h][i][0] = opaque(pack_bf16(acc[h][32 + 4 * i], acc[h][32 + 4 * i + 1]));
          vp[h][i][0] = movm(pack_bf16(acc[h][64 + 4 * i], acc[h][64 + 4 * i + 1]));
          qp[h][i][0] = opaque(pack_bf16(acc[h][4 * i], acc[h][4 * i + 1]));
          qp[h][i][1] = opaque(pack_bf16(acc[h][4 * i + 2], acc[h][4 * i + 3]));
        }
      }
      if (w == 0) {
        for (uint32_t it = 0; grp > 0 && it < POLL_MAX && __any_sync(~0u, empty(hk[0][0]) || empty(hk[0][1]) || empty(hw[0][0]) || empty(hw[0][1])); it++) {
#pragma unroll
          for (int d = 0; d < 2; d++) { hk[0][d] = ld_relaxed_v4(mbox + d * 32); hw[0][d] = ld_relaxed_v4(mbox + d * 32 + 64); }
        }
#pragma unroll
        for (int d = 0; d < 2; d++)
          hw[0][d] = first ? make_uint4(0, 0, 0, 0) : make_uint4(movm(hw[0][d].x), movm(hw[0][d].y), movm(hw[0][d].z), movm(hw[0][d].w));
      }
      const uint32_t hv[2][8] = {{hw[0][0].x, hw[0][0].y, hw[0][0].z, hw[0][0].w, hw[0][1].x, hw[0][1].y, hw[0][1].z, hw[0][1].w},
                                 {hw[1][0].x, hw[1][0].y, hw[1][0].z, hw[1][0].w, hw[1][1].x, hw[1][1].y, hw[1][1].z, hw[1][1].w}};
      landed(hw[0][0].x & hw[0][1].x & hw[1][0].x & hw[1][1].x);
      float s0[4][4], s1[4][4], s2[4][4];
#pragma unroll
      for (int c = 3; c >= 0; c--) {
        const int h = c >> 1, b = (c & 1) * 4;
        mma16816z(s1[c], qp[h][b][0], qp[h][b][1], qp[h][b + 1][0], qp[h][b + 1][1], kp[h][b][0], kp[h][b + 1][0]);
        mma16816z(s2[c], qp[h][b][0], qp[h][b][1], qp[h][b + 1][0], qp[h][b + 1][1], kp[h][b][1], kp[h][b + 1][1]);
        mma16816z(s0[c], qp[h][b][0], qp[h][b][1], qp[h][b + 1][0], qp[h][b + 1][1], hk[h][c & 1].x, hk[h][c & 1].y);
      }
#pragma unroll
      for (int c = 3; c >= 0; c--) {
        const int h = c >> 1, b = (c & 1) * 4 + 2;
        mma16816(s1[c], qp[h][b][0], qp[h][b][1], qp[h][b + 1][0], qp[h][b + 1][1], kp[h][b][0], kp[h][b + 1][0]);
        mma16816(s2[c], qp[h][b][0], qp[h][b][1], qp[h][b + 1][0], qp[h][b + 1][1], kp[h][b][1], kp[h][b + 1][1]);
        mma16816(s0[c], qp[h][b][0], qp[h][b][1], qp[h][b + 1][0], qp[h][b + 1][1], hk[h][c & 1].z, hk[h][c & 1].w);
      }
      arrive_after(bars + B_R + 16 * wg, s0[0][0]);
      const bool c0 = 2 * t <= g, c1 = 2 * t + 1 <= g;
      const uint32_t mcur = (c0 ? 0x0000ffffu : 0u) | (c1 ? 0xffff0000u : 0u);
      uint32_t pa[4], pb[4];
#pragma unroll
      for (int c = 3; c >= 0; c--) {
        if (c < 2 && first) { s0[c][0] = -INFINITY; s0[c][1] = -INFINITY; }
        float a0 = c0 ? s1[c][0] : s0[c][0], a1 = c1 ? s1[c][1] : s0[c][1];
        float b0 = c0 ? s2[c][2] : s1[c][2], b1 = c1 ? s2[c][3] : s1[c][3];
        const float ma = quad_max(fmaxf(a0, a1)), mb = quad_max(fmaxf(b0, b1));
        a0 = ex2((a0 - ma) * ATT_SCALE_LOG2E); a1 = ex2((a1 - ma) * ATT_SCALE_LOG2E);
        b0 = ex2((b0 - mb) * ATT_SCALE_LOG2E); b1 = ex2((b1 - mb) * ATT_SCALE_LOG2E);
        const float ia = rcp(quad_sum(a0 + a1)), ib = rcp(quad_sum(b0 + b1));
        pa[c] = opaque(pack_bf16(a0 * ia, a1 * ia)); pb[c] = opaque(pack_bf16(b0 * ib, b1 * ib));
      }
      if (pp.lead) { mbar_wait(bars + B_R + 16 * wg, 0); pp.release(ea.y); }
      float o[16][4];
#pragma unroll
      for (int i = 0; i < 16; i++) mma16816z(o[i], pa[i >> 2] & mcur, pb[i >> 2] & ~mcur, 0u, pb[i >> 2] & mcur, vp[i >> 3][i & 7][0], vp[i >> 3][i & 7][1]);
#pragma unroll
      for (int i = 0; i < 16; i++) mma1688(o[i], pa[i >> 2] & ~mcur, 0u, hv[i >> 3][i & 7]);
      arrive_after(bars + B_R + 16 * wg + 8, o[15][0]);
      uint4* tile = img + (T_O + wg * 16 + j) * 1024;
      uint4* dst = tile + img_pos(w, lane);
#pragma unroll
      for (int c = 0; c < 4; c++)
#pragma unroll
        for (int f = 0; f < 2; f++) {
          stg128(dst + c * 256 + f * 32, pack_bf16(o[4 * c][2 * f], o[4 * c][2 * f + 1]), pack_bf16(o[4 * c + 1][2 * f], o[4 * c + 1][2 * f + 1]),
                 pack_bf16(o[4 * c + 2][2 * f], o[4 * c + 2][2 * f + 1]), pack_bf16(o[4 * c + 3][2 * f], o[4 * c + 3][2 * f + 1]));
        }
      publish(ld_relaxed(tile + img_line(w, lane)), cnt + G_O, 1);
    }

    {
      float acc[2][64];
      uint32_t xr[32];
      {
        const uint32_t lane = tid_now() & 31;
        const uint2 e = pp.begin(17);
        const uint32_t a0 = sb + (e.x & 0xffff) * 16 + (w * 16 + (lane & 15)) * 128 + (((lane >> 4) ^ (lane & 7)) << 4);
#pragma unroll
        for (int i = 0; i < 8; i++) ldsm4((a0 ^ ((i & 3) << 5)) + (i >> 2) * 8192, xr[4 * i], xr[4 * i + 1], xr[4 * i + 2], xr[4 * i + 3]);
        landed(xr[0] & xr[4] & xr[8] & xr[12] & xr[16] & xr[20] & xr[24] & xr[28]);
        named_sync(1 + wg, 128);
        pp.release(e.y);
      }
      pp.prev = 0;
#pragma unroll 1
      for (int n = 18; n < 24; n++) {
        const uint2 e = pp.begin(n);
        const uint32_t da = e.x & 0xffff, db = dB0 + (e.x >> 16);
        wg_fence();
#pragma unroll
        for (int q = 0; q < 4; q++) {
          wg_n128<H64, H128>(acc[0], dAo + da + qa(q), db + 128 * q, q ? 1 : n - 18);
          wg_n128<H64, H128>(acc[1], dAp + da + qa(q), db + 128 * q, q ? 1 : n - 18);
        }
        wg_commit();
        pp.template end<true>(e.y);
      }
      const uint2 e0 = pp.begin(24);
      const uint2 e1 = pp.begin(25);
#pragma unroll
      for (int h = 1; h >= 0; h--) {
        wg_fence();
#pragma unroll
        for (int q = 0; q < 4; q++) wg_n128<H64, H128>(acc[h], (h ? dAp : dAo) + (e0.x & 0xffff) + qa(q), dB0 + (e0.x >> 16) + 128 * q, 1);
#pragma unroll
        for (int q = 0; q < 4; q++) wg_n128<H64, H128>(acc[h], (h ? dAp : dAo) + (e1.x & 0xffff) + qa(q), dB0 + (e1.x >> 16) + 128 * q, 1);
        wg_commit();
      }
      const uint32_t tid = tid_now() & 127, lane = tid & 31;
      const uint2 ea = pp.begin(26);
      const uint32_t px = (ea.x & 0xffff) * 16 + tid * 16;
      wg_wait<1>();
      pp.release_now(pp.prev);
      fence_regs(acc[1]);
#pragma unroll
      for (int i = 0; i < 8; i++)
        st_async(pp.peer_bars - BAR_OFF + px + i * 2048, pp.peer_bars + (pp.nx.y & 0x3ff), pack_bf16(acc[1][8 * i], acc[1][8 * i + 1]), pack_bf16(acc[1][8 * i + 2], acc[1][8 * i + 3]),
                 pack_bf16(acc[1][8 * i + 4], acc[1][8 * i + 5]), pack_bf16(acc[1][8 * i + 6], acc[1][8 * i + 7]));
      wg_wait<0>();
      pp.release(e0.y); pp.release(e1.y); pp.release_now(ea.y);
      fence_regs(acc[0]);
      const uint32_t ep = tag_of(lds32(bars + ROLE_OFF + 4));
      mbar_wait(bars + B_PAR, 0);
      uint32_t pr[3][16];
#pragma unroll
      for (int i = 0; i < 4; i++) {
        const uint4 x = lds128(sb + PAR_OFF + (i >> 2) * 256 + (lane & 3) * 64 + (i & 3) * 16);
        pr[i >> 2][(i & 3) * 4] = x.x; pr[i >> 2][(i & 3) * 4 + 1] = x.y; pr[i >> 2][(i & 3) * 4 + 2] = x.z; pr[i >> 2][(i & 3) * 4 + 3] = x.w;
      }
      const uint2 eb = pp.begin(27);
      float sm[2] = {0.f, 0.f}, sq[2] = {0.f, 0.f};
#pragma unroll
      for (int c = 0; c < 8; c++) {
        const uint4 z = lds128(sb + px + c * 2048);
        const uint32_t zz[4] = {z.x, z.y, z.z, z.w};
#pragma unroll
        for (int b = 0; b < 4; b++) {
          const int i = 4 * c + b;
          xr[i] = hfma2_bf16(pr[0][i >> 1], hadd2_bf16(pack_bf16(acc[0][2 * i], acc[0][2 * i + 1]), zz[b]), xr[i]);
          const float d0 = bf_lo(xr[i]), d1 = bf_hi(xr[i]);
          acc[0][2 * i] = d0; acc[0][2 * i + 1] = d1;
          sm[i & 1] += d0 + d1;
          sq[i & 1] = fmaf(d0, d0, fmaf(d1, d1, sq[i & 1]));
        }
      }
      {
        const bool b0 = lane & 1;
        sm[0] = (b0 ? sm[1] : sm[0]) + __shfl_xor_sync(~0u, b0 ? sm[0] : sm[1], 1);
        sq[0] = (b0 ? sq[1] : sq[0]) + __shfl_xor_sync(~0u, b0 ? sq[0] : sq[1], 1);
        sm[0] += __shfl_xor_sync(~0u, sm[0], 2);
        sq[0] += __shfl_xor_sync(~0u, sq[0], 2);
      }
      uint2* ss = Q.s->stat + (rb * 2 + rank) * 512 + w * 16 + (lane >> 2) * 2 + (lane & 1);
      if (!(lane & 2)) st_relaxed_b64(ss + (j >> 1) * 64, tagf(sm[0], ep), tagf(sq[0], ep));
      named_sync(1 + wg, 128);
      pp.release(eb.y);
      mbar_wait(bars + B_PAR + 8, 0);
#pragma unroll
      for (int i = 4; i < 12; i++) {
        const uint4 x = lds128(sb + PAR_OFF + (i >> 2) * 256 + (lane & 3) * 64 + (i & 3) * 16);
        pr[i >> 2][(i & 3) * 4] = x.x; pr[i >> 2][(i & 3) * 4 + 1] = x.y; pr[i >> 2][(i & 3) * 4 + 2] = x.z; pr[i >> 2][(i & 3) * 4 + 3] = x.w;
      }
      {
        ss += (lane & 2) * 128;
        uint2 p[4];
#pragma unroll
        for (int i = 0; i < 4; i++) p[i] = make_uint2(0, 0);
        spin(DELAY_ST);
        uint32_t it = 0, bad;
        do {
          bad = 0;
#pragma unroll
          for (int i = 0; i < 4; i++) if (((p[i].x ^ ep) | (p[i].y ^ ep)) & 3u) p[i] = ld_relaxed_b64(ss + i * 64);
#pragma unroll
          for (int i = 0; i < 4; i++) bad |= (p[i].x ^ ep) | (p[i].y ^ ep);
        } while (__any_sync(~0u, bad & 3u) && ++it < POLL_MAX);
        float m = (__uint_as_float(p[0].x) + __uint_as_float(p[1].x)) + (__uint_as_float(p[2].x) + __uint_as_float(p[3].x));
        float v = (__uint_as_float(p[0].y) + __uint_as_float(p[1].y)) + (__uint_as_float(p[2].y) + __uint_as_float(p[3].y));
        m += __shfl_xor_sync(~0u, m, 2); v += __shfl_xor_sync(~0u, v, 2);
        m *= 1.f / D_;
        v = rsqrtf(fmaxf(fmaf(-m, m, v * (1.f / D_)), 0.f) + 1e-5f);
        m = -m * v;
#pragma unroll
        for (int r = 0; r < 2; r++) { sm[r] = __shfl_sync(~0u, m, r, 2); sq[r] = __shfl_sync(~0u, v, r, 2); }
      }
      uint4* tile = img + (T_H + wg * 16 + (j & 14)) * 1024 + rank * 512;
      uint4* dst = tile + img_pos(w, lane);
#pragma unroll
      for (int c = 0; c < 4; c++)
#pragma unroll
        for (int f = 0; f < 2; f++) {
          uint32_t y[4];
#pragma unroll
          for (int b = 0; b < 4; b++) {
            const int i = c * 4 + b;
            y[b] = hfma2_bf16(pack_bf16(fmaf(acc[0][4 * i + 2 * f], sq[f], sm[f]), fmaf(acc[0][4 * i + 2 * f + 1], sq[f], sm[f])), pr[2][i], pr[1][i]);
          }
          stg128(dst + (c >> 1) * 1024 + (c & 1) * 256 + f * 32, y[0], y[1], y[2], y[3]);
        }
      publish(ld_relaxed(tile + img_line(w, lane) + (lane >> 4) * 512), cnt + G_H2, 1);
#pragma unroll
      for (int c = 0; c < 4; c++)
#pragma unroll
        for (int f = 0; f < 2; f++) {
          stg128(dst + (T_X1 - T_H + (c >> 1)) * 1024 + (c & 1) * 256 + f * 32, xr[8 * c + f], xr[8 * c + 2 + f], xr[8 * c + 4 + f], xr[8 * c + 6 + f]);
        }
    }

    float acc[2][64], ax[32];
    uint32_t px_y;
    {
      float a3[2][96];
      pp.prev = 0;
#pragma unroll 1
      for (int n = 28; n < 44; n++) {
        const uint2 e = pp.begin(n);
        const uint32_t da = e.x & 0xffff, db = dB0 + (e.x >> 16);
        wg_fence();
#pragma unroll
        for (int q = 0; q < 4; q++) {
          wg_n192<H64, H128>(a3[0], dAo + da + qa(q), db + 128 * q, q ? 1 : n - 28);
          wg_n192<H64, H128>(a3[1], dAp + da + qa(q), db + 128 * q, q ? 1 : n - 28);
        }
        wg_commit();
        pp.end(e.y);
      }
      px_y = pp.nx.y;
      pp.nx = pp.tab[45]; pp.ready = false;
      mbar_wait(bars + ((px_y >> 16) & 0x7ff), px_y >> 31);
      wg_wait<0>();
      pp.release_now(pp.prev);
      fence_regs(a3[0]); fence_regs(a3[1]);
      pp.prev = 0;
#pragma unroll
      for (int i = 0; i < 4; i++)
        st_async(pp.peer_bars - 8192 + (tid_now() & 127) * 16 + i * 2048, pp.peer_bars + (px_y & 0x3ff), pack_bf16(a3[1][64 + 8 * i], a3[1][65 + 8 * i]),
                 pack_bf16(a3[1][66 + 8 * i], a3[1][67 + 8 * i]), pack_bf16(a3[1][68 + 8 * i], a3[1][69 + 8 * i]), pack_bf16(a3[1][70 + 8 * i], a3[1][71 + 8 * i]));
#pragma unroll
      for (int i = 0; i < 64; i++) { acc[0][i] = a3[0][i]; acc[1][i] = a3[1][i]; }
#pragma unroll
      for (int i = 0; i < 32; i++) ax[i] = a3[0][64 + i];
    }
    uint32_t seen, seen2;
#pragma unroll 1
    for (int T = 0;; T++) {
      wg_wait<0>();
      pp.release_now(pp.prev);
      fence_regs(acc[0]); fence_regs(acc[1]);
      pp.prev = 0;
      {
        const uint32_t lane = tid_now() & 31;
        uint4* tile = img + (T_ACT + wg * 56 + (T ? 8 + 16 * T : 0) + j) * 1024;
        uint4* tx = img + (T_ACT + wg * 56 + 16 + (j >> 1)) * 1024 + rank * 512;
        const int ts = (int)clock();
#pragma unroll
        for (int c = 0; c < 4; c++)
#pragma unroll
          for (int f = 0; f < 2; f++) {
            uint32_t y[4];
#pragma unroll
            for (int b = 0; b < 4; b++) {
              const int i = ((c & 1) * 4 + b) * 4 + 2 * f;
              y[b] = pack_bf16(swiglu(acc[c >> 1][i], acc[c >> 1][i] * acc[c >> 1][32 + i]), swiglu(acc[c >> 1][i + 1], acc[c >> 1][i + 1] * acc[c >> 1][33 + i]));
            }
            stg128(tile + img_pos(w, lane) + ((c >> 1) ^ rank) * 512 + (c & 1) * 256 + f * 32, y[0], y[1], y[2], y[3]);
            if (c + f < 4) until(ts, (2 * c + f + 1) * P_ACT);
            fence_regs(acc[0]); fence_regs(acc[1]);
          }
        if (T == 0) {
          if (wg == 0 && j < N_HK) publish(ld_relaxed(tile + img_line(w, lane)), cnt + G_HK, 1);
          mbar_wait(bars + (px_y & 0x3ff), 1);
          uint32_t z[16];
#pragma unroll
          for (int i = 0; i < 4; i++) { const uint4 x = lds128(bars - 8192 + (tid_now() & 127) * 16 + i * 2048); z[4 * i] = x.x; z[4 * i + 1] = x.y; z[4 * i + 2] = x.z; z[4 * i + 3] = x.w; }
          landed(z[0] & z[4] & z[8] & z[12]);
          named_sync(1 + wg, 128);
          pp.release(px_y);
#pragma unroll
          for (int c = 0; c < 2; c++)
#pragma unroll
            for (int f = 0; f < 2; f++) {
              uint32_t y[4];
#pragma unroll
              for (int b = 0; b < 4; b++) {
                const int i = (c * 4 + b) * 2 + f;
                const float o0 = bf_lo(z[i]), o1 = bf_hi(z[i]);
                y[b] = pack_bf16(swiglu(rank ? o0 : ax[2 * i], o0 * ax[2 * i]), swiglu(rank ? o1 : ax[2 * i + 1], o1 * ax[2 * i + 1]));
              }
              stg128(tx + img_pos(w, lane) + c * 256 + f * 32, y[0], y[1], y[2], y[3]);
            }
        }
        seen = ld_relaxed(tile + img_line(w, lane));
        seen2 = ld_relaxed(tx + img_line(w, lane & 15));
      }
      if (T == 2) break;
      const int n0 = 45 + 16 * T, n1 = n0 + 16;
#pragma unroll 1
      for (int n = n0; n < n1; n++) {
        const uint2 e = pp.begin(n);
        const uint32_t da = e.x & 0xffff, db = dB0 + (e.x >> 16);
        wg_fence();
#pragma unroll
        for (int q = 0; q < 4; q++) {
          wg_n128<H64, H128>(acc[0], dAo + da + qa(q), db + 128 * q, q ? 1 : n - n0);
          wg_n128<H64, H128>(acc[1], dAp + da + qa(q), db + 128 * q, q ? 1 : n - n0);
        }
        wg_commit();
        if (n == n0 + 1) publish(opaque(seen) & opaque(seen2), cnt + G_ACT + T, 1);
        pp.end(e.y);
      }
    }
    {
      float gf[32];
#pragma unroll
      for (int ph = 0; ph < 2; ph++) {
#pragma unroll 1
        for (int n = ph ? 90 : 77; n < (ph ? N_END : 90); n++) {
          const uint2 e = pp.begin(n);
          const uint32_t da = dA0 + wg * 512 + (e.x & 0xffff), db = dB0 + (e.x >> 16);
          wg_fence();
#pragma unroll
          for (int q = 0; q < 4; q++) wg_n128<H64, H128>(acc[0], da + qa(q), db + 128 * q, q || ph ? 1 : n - 77);
          wg_commit();
          pp.end(e.y);
        }
        if (ph == 0) {
          publish(opaque(seen) & opaque(seen2), cnt + G_ACT + 2, 1);
          mbar_wait(bars + B_GB, 0);
#pragma unroll
          for (int i = 0; i < 4; i++) {
            const uint4 x = lds128(sb + PAR_OFF + 768 + (tid_now() & 3) * 64 + i * 16);
            const uint32_t g4[4] = {x.x, x.y, x.z, x.w};
#pragma unroll
            for (int b = 0; b < 4; b++) { gf[8 * i + 2 * b] = bf_lo(g4[b]); gf[8 * i + 2 * b + 1] = bf_hi(g4[b]); }
          }
          fence_regs(gf);
        }
      }
      const uint32_t lane = tid_now() & 31;
      {
        const uint2 e0 = pp.begin(N_END), e1 = pp.begin(N_END + 1);
#pragma unroll
        for (int i = 0; i < 8; i++) {
          const uint4 r = lds128(sb + (((i & 4 ? e1.x : e0.x) & 0xffff) + wg * 512 + img_pos(w, lane) + ((i >> 1) & 1) * 256 + (i & 1) * 32) * 16);
          const uint32_t x[4] = {r.x, r.y, r.z, r.w};
#pragma unroll
          for (int b = 0; b < 4; b++) { acc[1][(i >> 1) * 16 + 4 * b + 2 * (i & 1)] = bf_lo(x[b]); acc[1][(i >> 1) * 16 + 4 * b + 2 * (i & 1) + 1] = bf_hi(x[b]); }
        }
      }
      const uint32_t st = sb + ((w & 2) ? pp.nx.x >> 16 : pp.nx.x & 0xffff) * 16 + wg * 8192 + (w & 1) * 4096;
      const uint32_t a0 = opaque(st + (lane & 15) * 128 + (((lane >> 4) ^ (lane & 7)) << 4));
      if (pp.lead && elect_one()) mbar_arrive(bars + B_END);
      wg_wait<0>();
      pp.release_now(pp.prev);
      fence_regs(acc[0]);
#pragma unroll
      for (int c = 0; c < 4; c++) {
        uint32_t y[2][4];
#pragma unroll
        for (int f = 0; f < 2; f++)
#pragma unroll
          for (int b = 0; b < 4; b++) {
            const int i = 16 * c + 4 * b + 2 * f;
            y[f][b] = pack_bf16(fmaf(gf[8 * c + 2 * b], acc[0][i], acc[1][i]), fmaf(gf[8 * c + 2 * b + 1], acc[0][i + 1], acc[1][i + 1]));
          }
        stsm4((a0 ^ ((c & 1) << 6)) + (c >> 1) * 2048, y[0][0], y[1][0], y[0][1], y[1][1]);
        stsm4((a0 ^ ((c & 1) << 6) ^ 32) + (c >> 1) * 2048, y[0][2], y[1][2], y[0][3], y[1][3]);
        if (c == 1) {
          fence_async_smem(); __syncwarp();
          if (elect_one()) {
            tma2d_st(&P.mOut, st, typ * D_ + (j & 7) * 128, grp * 128 + wg * 64 + w * 16);
            bulk_commit();
          }
        }
      }
      {
        __syncwarp();
        const uint32_t ln = tid_now() & 31;
        uint4* op = (uint4*)(Q.out + (size_t)(grp * 256 + 2 * (wg * 64 + w * 16 + (ln >> 3)) + typ) * D_ + (j & 7) * 128 + 64) + (ln & 7);
        uint4 r[4];
#pragma unroll
        for (int k = 0; k < 4; k++) r[k] = lds128(st + 2048 + ((ln >> 3) + 4 * k) * 128 + (((ln & 7) ^ (((ln >> 3) + 4 * k) & 7)) << 4));
#pragma unroll
        for (int k = 0; k < 4; k++) stg128(op + k * D_, r[k].x, r[k].y, r[k].z, r[k].w);
        if (elect_one()) bulk_wait_read();
      }
    }
  } else {
    asm volatile("setmaxnreg.dec.sync.aligned.u32 40;");
    const uint32_t lane = tid_now() & 31;
    if (elect_one()) {
      if (warp == 10) {
        prefetch_tmap(&P.mWqkv);
#pragma unroll
        for (int i = 0; i < 12; i++) mbar_init(bars + 1024 + 8 * i, i < 4 ? 4 : 1);
        mbar_init(bars + B_ST, 4); mbar_init(bars + B_ST + 8, 8); mbar_init(bars + B_XB, 1); mbar_init(bars + B_XB + 8, 1); mbar_init(bars + B_END, 2);
        sts32(bars + ROLE_OFF, cta >> 1);
      } else if (warp == 11) {
#pragma unroll 1
        for (int u = 0; u < 2; u++) {
#pragma unroll
          for (int i = 0; i < 20; i++) mbar_init(bars + u * 512 + 352 + 8 * i, 1 + u);
        }
      } else {
#pragma unroll 22
        for (int i = 0; i < 44; i++) mbar_init(bars + (warp & 1) * 512 + 8 * i, 1 + (warp & 1));
      }
      asm volatile("fence.mbarrier_init.release.cluster;" ::: "memory");
    }
    named_sync(0, NTHREADS);
    asm volatile("barrier.cluster.arrive.relaxed.aligned;" ::: "memory");
    asm volatile("barrier.cluster.wait.aligned;" ::: "memory");
    const uint32_t ep0 = ld_relaxed(&Q.s->ep[cta * 32 + lane]);
    if (!(warp & 1)) {
      if (only_one()) {
        const int q = (warp >> 1) & 1;
        const uint2* tab = c_act[q];
        const char* src = (const char*)(Q.s->img + (size_t)grp * (N_TILES * 1024) + rank * 512);
        const uint32_t sa = sb + rank * 8192;
        if (q) {
          if (cta >= 64) {
#pragma unroll 1
            for (int i = 0; i < 4; i++) {
              until(t0, (cta >= 96 ? T_Q3 : T_Q2) + i * P_Q);
              mbar_expect_tx(bars + B_SL + 8 * i, 8192);
              tma2d_once(sb + SL_OFF + i * 8192, &P.mWm2, bars + B_SL + 8 * i, ((cta >> 4) & 1) * D_ + (cta >> 5) * 256 + ((cta >> 2) & 3) * 64, (cta & 3) * 256 + i * 64);
            }
          }
        }
        mbar_expect_tx(bars + B_XB + 8 * q, 16384);
#pragma unroll 1
        for (int i = 0; i < 8; i++) {
          until(t0, q ? T_XB + i * P_XB : T_XA);
          bulk_g2s(sb + (4 + q) * 16384 + i * 2048, Q.x + (size_t)(cta * 16 + 2 * i + q) * D_, 2048, bars + B_XB + 8 * q);
        }
        const uint32_t target = (opaque(ep0) + 1) * 64;
        const uint32_t* cnt = Q.s->cnt + grp * 32;
        const char* x1 = src + (T_X1 + typ * 16 + (j & 7) * 2) * 16384 + (q - rank) * 8192;
        uint2 nx = tab[0];
#pragma unroll 1
        for (int ph = 0; ph < 4; ph++) {
          const bool half = ph == 3;
          tiles<1>(bars, tab, nx, half ? 77 : (ph ? 11 + 17 * ph : 0), half ? N_END : (ph ? 11 + 33 * ph : 16), half ? sb + q * 8192 + rank * 4096 : sa,
                   half ? src + typ * 56 * 16384 + q * 8192 - rank * 4096 : src, half ? 4096 : 8192, half ? cnt + typ * 8 : cnt, target, 0, 0);
          if (ph == 1) { mbar_expect_tx(bars + (nx.y & 0x3ff), 8192); nx = tab[45]; }
          if (ph) continue;
#pragma unroll 1
          for (int n = 16; n < 28; n++) {
            const uint2 e = nx;
            nx = tab[n + 1];
            const uint32_t fb = bars + (e.y & 0x3ff);
            mbar_wait(bars + (e.x & 0x7ff), e.x >> 31);
            mbar_expect_tx(fb, (e.y >> 29) << 13);
            if (n == 17) {
              tma2d(sb + (e.y & 0x3c000), &P.mX, fb, q * D_ + (j & 14) * 64, grp * 128 + rank * 64);
              tma2d(sb + (e.y & 0x3c000) + 8192, &P.mX, fb, q * D_ + (j | 1) * 64, grp * 128 + rank * 64);
              tiles<0>(bars, tab, nx, 18, 26, sb, src + rank * 8192, 16384, cnt, target, q ? P_G2B : P_G2, q ? F_G2B : F_G2A);
              n = 25;
            }
          }
        }
        while ((int32_t)(ld_relaxed_line(cnt + G_X1) - target) < 0) {}
        asm volatile("fence.acquire.gpu;" ::: "memory"); fence_async_glob();
#pragma unroll 1
        for (int n = 0; n < 2; n++) {
          const uint2 e = tab[N_END + n];
          const uint32_t fb = bars + (e.y & 0x3ff);
          mbar_expect_tx(fb, 8192);
          mbar_wait(bars + (e.x & 0x7ff), e.x >> 31);
          bulk_g2s(sb + q * 8192 + (e.y & 0x3c000), x1 + n * 16384, 8192, fb);
        }
      }
    } else if (warp == 9) {
      if (only_one()) {
        uint2 nx = c_w[0][0];
#pragma unroll 1
        for (int n = 0; n < N_W;) {
          if (n < 5) until(t0, n ? T_W + (n - 1) * P_W : T_W0);
          if (n == 2) mbar_wait(bars + B_SLE, 0);
          if (n == 5) { prefetch_tmap(&P.mWo); prefetch_tmap(&P.mWg); prefetch_tmap(&P.mWu); prefetch_tmap(&P.mWd); prefetch_tmap(&P.mX); }
          const int u = (nx.y >> 10) & 7;
          if (u < 2) {
            weights<3>(sb, nx, n, u ? &P.mWg : &P.mWqkv, u ? &P.mWu : &P.mWqkv, u ? &P.mWg + rank : &P.mWqkv,
                       j * 64, (u ? 0 : D_) + j * 64, u ? 1024 + (j >> 1) * 64 : 2 * D_ + j * 64, 0);
          } else {
            const bool ffn = u == 3 || u == 4;
            const int c0 = ffn ? u * 1024 - 1536 + j * 64 : (u == 2 ? j >> 1 : j & 7) * 128;
            const CUtensorMap* m0 = ffn ? &P.mWg : (u == 2 ? &P.mWo : &P.mWd);
            weights<2>(sb, nx, n, m0, m0 + ffn, nullptr, c0, ffn ? c0 : c0 + 64, 0, u == 2 ? rank * 2 : 0);
          }
        }
        prefetch_tmap(&P.mOut);
      }
    } else {
      {
        const uint32_t i = opaque((grp * 2 + rank) * 8), k = i < N_W - 128 ? i + 128 : 128;
        if ((c_cons[0][i].x & c_cons[1][i].x & c_act[0][i].y & c_act[1][i].y & c_w[0][i].y & c_w[0][k].y) == 0xffffffffu) __trap();
      }
      const uint32_t ep = opaque(ep0) + 1;
      if (lane == 0) {
        sts32(bars + ROLE_OFF + 4, ep);
        uint32_t pr; asm volatile("ld.shared::cluster.u32 %0, [%1];" : "=r"(pr) : "r"(mapa(bars + ROLE_OFF, rank ^ 1)) : "memory");
        if (pr != (uint32_t)(cta >> 1) || sb != smem_u32(smem_raw)) { __trap(); }
      }
      const uint32_t tag = tag_of(ep);
#pragma unroll 1
      for (int i = 0; i < 8; i++) {
        const uint2* src = (const uint2*)(Q.s->modp + (i >> 1) * 1024 + (i < 6 ? j >> 1 : j & 7) * 128 + (i & 1) * 64) + lane;
        uint2 a; uint32_t it = 0;
        do { if (it) __nanosleep(200); a = ld_relaxed_b64(src); guard(++it); } while (__any_sync(~0u, ((a.x ^ tag) | (a.y ^ tag)) & 3u));
        uint32_t p = pack_bf16(__uint_as_float(a.x), __uint_as_float(a.y));
        if ((i >> 1) == 2) p = pack_bf16(1.f + bf_lo(p), 1.f + bf_hi(p));
        const float sc = i < 2 ? 1.f : (i < 6 ? 0.5f : 2.f);
        p = pack_bf16(sc * bf_lo(p), sc * bf_hi(p));
        sts32(sb + PAR_OFF + (i >> 1) * 256 + (lane & 3) * 64 + (i & 1) * 32 + (lane >> 2) * 4, p);
        __syncwarp();
        if ((i == 1 || i == 5 || i == 7) && elect_one()) { mbar_arrive(bars + (i == 7 ? B_GB : B_PAR + (i & 4) * 2)); }
      }
      mbar_wait_bounded(bars + B_R, 0);
      Q.s->ep[cta * 32 + lane] = ep;
      mbar_wait_bounded(bars + B_END, 0);
    }
  }
}

typedef CUresult (*PFN_encodeTiled)(CUtensorMap*, CUtensorMapDataType, cuuint32_t, void*, const cuuint64_t*, const cuuint64_t*,
                                    const cuuint32_t*, const cuuint32_t*, CUtensorMapInterleave, CUtensorMapSwizzle,
                                    CUtensorMapL2promotion, CUtensorMapFloatOOBfill);

void make_map(PFN_encodeTiled enc, CUtensorMap* m, const void* ptr, uint64_t inner, uint64_t outer, uint32_t box_outer, int promo = CU_TENSOR_MAP_L2_PROMOTION_L2_256B) {
  cuuint64_t dims[2] = {inner, outer};
  cuuint64_t strides[1] = {inner * 2};
  cuuint32_t box[2] = {64, box_outer};
  cuuint32_t es[2] = {1, 1};
  enc(m, CU_TENSOR_MAP_DATA_TYPE_BFLOAT16, 2, const_cast<void*>(ptr), dims, strides, box, es, CU_TENSOR_MAP_INTERLEAVE_NONE,
      CU_TENSOR_MAP_SWIZZLE_128B, (CUtensorMapL2promotion)promo, CU_TENSOR_MAP_FLOAT_OOB_FILL_NONE);
}
void make_wmap(PFN_encodeTiled enc, CUtensorMap* m, const void* ptr, uint64_t cols, uint64_t rows, bool permuted) {
  cuuint64_t dims[5] = {cols, 2, 4, 4, rows / 32};
  cuuint64_t strides[4] = {cols * 2, cols * 2 * (permuted ? 8 : 2), cols * 2 * (permuted ? 2 : 8), cols * 2 * 32};
  cuuint32_t box[5] = {64, 2, 4, 4, 2};
  cuuint32_t es[5] = {1, 1, 1, 1, 1};
  enc(m, CU_TENSOR_MAP_DATA_TYPE_BFLOAT16, 5, const_cast<void*>(ptr), dims, strides, box, es, CU_TENSOR_MAP_INTERLEAVE_NONE,
      CU_TENSOR_MAP_SWIZZLE_128B, CU_TENSOR_MAP_L2_PROMOTION_L2_128B, CU_TENSOR_MAP_FLOAT_OOB_FILL_NONE);
}

}

extern "C" void kernel_launch(void* const* d_in, const int* in_sizes, int n_in, void* d_out, int out_size) {
  (void)in_sizes; (void)n_in; (void)out_size;
  static PFN_encodeTiled enc = nullptr;
  static void* scratch = nullptr;
  static int sms = 0;
  if (!enc) {
    int dev = 0;
    cudaGetDevice(&dev);
    cudaDeviceGetAttribute(&sms, cudaDevAttrMultiProcessorCount, dev);
    cudaGetSymbolAddress(&scratch, g_s);
    void* fn = nullptr;
    cudaDriverEntryPointQueryResult q;
    cudaGetDriverEntryPoint("cuTensorMapEncodeTiled", &fn, cudaEnableDefault, &q);
    enc = (PFN_encodeTiled)fn;
    cudaFuncSetAttribute(fused_kernel<true>, cudaFuncAttributeMaxDynamicSharedMemorySize, SMEM_BYTES);
    cudaFuncSetAttribute(fused_kernel<false>, cudaFuncAttributeMaxDynamicSharedMemorySize, SMEM_BYTES);
  }
  Params P;
  make_wmap(enc, &P.mWqkv, d_in[1], 3 * D_, D_, false);
  make_wmap(enc, &P.mWo, d_in[2], D_, D_, true);
  make_wmap(enc, &P.mWg, d_in[4], F_, D_, true);
  make_wmap(enc, &P.mWu, d_in[5], F_, D_, true);
  make_wmap(enc, &P.mWd, d_in[6], D_, F_, true);
  make_map(enc, &P.mOut, d_out, 2 * D_, S_ / 2, 16);
  make_map(enc, &P.mX, d_in[0], 2 * D_, S_ / 2, 64, CU_TENSOR_MAP_L2_PROMOTION_L2_128B);
  make_map(enc, &P.mWm2, d_in[8], 6 * D_, D_, 64, CU_TENSOR_MAP_L2_PROMOTION_L2_128B);
  Ptrs Q;
  Q.s = (Scratch*)scratch;
  Q.x = (const __nv_bfloat16*)d_in[0];
  Q.c = (const __nv_bfloat16*)d_in[7];
  Q.out = (__nv_bfloat16*)d_out;
  if (sms == NCTA + 4) fused_kernel<true><<<NCTA + 4, NTHREADS, SMEM_BYTES, cudaStreamPerThread>>>(Q, P);
  else fused_kernel<false><<<NCTA + 4, NTHREADS, SMEM_BYTES, cudaStreamPerThread>>>(Q, P);
}
```

```cpp
#include <cuda_runtime.h>
#include <cuda.h>
#include <cuda_bf16.h>
#include <stdint.h>
#include <stddef.h>
#include <string.h>
#include <math.h>

template <uint32_t HA, uint32_t HB> __device__ __forceinline__ void wg_n128(float (&d)[64], uint32_t descA, uint32_t descB, int scaleD) {
  asm volatile("{\n.reg .pred p;\n.reg .b64 da, db;\n"
    "mov.b64 da, {%64, %67};\nmov.b64 db, {%65, %68};\n"
    "setp.ne.b32 p, %66, 0;\n"
    "wgmma.mma_async.sync.aligned.m64n128k16.f32.bf16.bf16 "
    "{%0, %1, %2, %3, %4, %5, %6, %7, %8, %9, %10, %11, %12, %13, %14, %15, "
    "%16, %17, %18, %19, %20, %21, %22, %23, %24, %25, %26, %27, %28, %29, %30, %31, "
    "%32, %33, %34, %35, %36, %37, %38, %39, %40, %41, %42, %43, %44, %45, %46, %47, "
    "%48, %49, %50, %51, %52, %53, %54, %55, %56, %57, %58, %59, %60, %61, %62, %63}, "
    "da, db, p, 1, 1, 0, 1;\n}\n"
    : "+f"(d[0]), "+f"(d[1]), "+f"(d[2]), "+f"(d[3]), "+f"(d[4]), "+f"(d[5]), "+f"(d[6]), "+f"(d[7]),
      "+f"(d[8]), "+f"(d[9]), "+f"(d[10]), "+f"(d[11]), "+f"(d[12]), "+f"(d[13]), "+f"(d[14]), "+f"(d[15]),
      "+f"(d[16]), "+f"(d[17]), "+f"(d[18]), "+f"(d[19]), "+f"(d[20]), "+f"(d[21]), "+f"(d[22]), "+f"(d[23]),
      "+f"(d[24]), "+f"(d[25]), "+f"(d[26]), "+f"(d[27]), "+f"(d[28]), "+f"(d[29]), "+f"(d[30]), "+f"(d[31]),
      "+f"(d[32]), "+f"(d[33]), "+f"(d[34]), "+f"(d[35]), "+f"(d[36]), "+f"(d[37]), "+f"(d[38]), "+f"(d[39]),
      "+f"(d[40]), "+f"(d[41]), "+f"(d[42]), "+f"(d[43]), "+f"(d[44]), "+f"(d[45]), "+f"(d[46]), "+f"(d[47]),
      "+f"(d[48]), "+f"(d[49]), "+f"(d[50]), "+f"(d[51]), "+f"(d[52]), "+f"(d[53]), "+f"(d[54]), "+f"(d[55]),
      "+f"(d[56]), "+f"(d[57]), "+f"(d[58]), "+f"(d[59]), "+f"(d[60]), "+f"(d[61]), "+f"(d[62]), "+f"(d[63])
    : "r"(descA), "r"(descB), "r"(scaleD), "n"(HA), "n"(HB));
}
template <uint32_t HA, uint32_t HB> __device__ __forceinline__ void wg_n192(float (&d)[96], uint32_t descA, uint32_t descB, int scaleD) {
  asm volatile("{\n.reg .pred p;\n.reg .b64 da, db;\n"
    "mov.b64 da, {%96, %99};\nmov.b64 db, {%97, %100};\n"
    "setp.ne.b32 p, %98, 0;\n"
    "wgmma.mma_async.sync.aligned.m64n192k16.f32.bf16.bf16 "
    "{%0, %1, %2, %3, %4, %5, %6, %7, %8, %9, %10, %11, %12, %13, %14, %15, "
    "%16, %17, %18, %19, %20, %21, %22, %23, %24, %25, %26, %27, %28, %29, %30, %31, "
    "%32, %33, %34, %35, %36, %37, %38, %39, %40, %41, %42, %43, %44, %45, %46, %47, "
    "%48, %49, %50, %51, %52, %53, %54, %55, %56, %57, %58, %59, %60, %61, %62, %63, "
    "%64, %65, %66, %67, %68, %69, %70, %71, %72, %73, %74, %75, %76, %77, %78, %79, "
    "%80, %81, %82, %83, %84, %85, %86, %87, %88, %89, %90, %91, %92, %93, %94, %95}, "
    "da, db, p, 1, 1, 0, 1;\n}\n"
    : "+f"(d[0]), "+f"(d[1]), "+f"(d[2]), "+f"(d[3]), "+f"(d[4]), "+f"(d[5]), "+f"(d[6]), "+f"(d[7]),
      "+f"(d[8]), "+f"(d[9]), "+f"(d[10]), "+f"(d[11]), "+f"(d[12]), "+f"(d[13]), "+f"(d[14]), "+f"(d[15]),
      "+f"(d[16]), "+f"(d[17]), "+f"(d[18]), "+f"(d[19]), "+f"(d[20]), "+f"(d[21]), "+f"(d[22]), "+f"(d[23]),
      "+f"(d[24]), "+f"(d[25]), "+f"(d[26]), "+f"(d[27]), "+f"(d[28]), "+f"(d[29]), "+f"(d[30]), "+f"(d[31]),
      "+f"(d[32]), "+f"(d[33]), "+f"(d[34]), "+f"(d[35]), "+f"(d[36]), "+f"(d[37]), "+f"(d[38]), "+f"(d[39]),
      "+f"(d[40]), "+f"(d[41]), "+f"(d[42]), "+f"(d[43]), "+f"(d[44]), "+f"(d[45]), "+f"(d[46]), "+f"(d[47]),
      "+f"(d[48]), "+f"(d[49]), "+f"(d[50]), "+f"(d[51]), "+f"(d[52]), "+f"(d[53]), "+f"(d[54]), "+f"(d[55]),
      "+f"(d[56]), "+f"(d[57]), "+f"(d[58]), "+f"(d[59]), "+f"(d[60]), "+f"(d[61]), "+f"(d[62]), "+f"(d[63]),
      "+f"(d[64]), "+f"(d[65]), "+f"(d[66]), "+f"(d[67]), "+f"(d[68]), "+f"(d[69]), "+f"(d[70]), "+f"(d[71]),
      "+f"(d[72]), "+f"(d[73]), "+f"(d[74]), "+f"(d[75]), "+f"(d[76]), "+f"(d[77]), "+f"(d[78]), "+f"(d[79]),
      "+f"(d[80]), "+f"(d[81]), "+f"(d[82]), "+f"(d[83]), "+f"(d[84]), "+f"(d[85]), "+f"(d[86]), "+f"(d[87]),
      "+f"(d[88]), "+f"(d[89]), "+f"(d[90]), "+f"(d[91]), "+f"(d[92]), "+f"(d[93]), "+f"(d[94]), "+f"(d[95])
    : "r"(descA), "r"(descB), "r"(scaleD), "n"(HA), "n"(HB));
}
template <uint32_t HA, uint32_t HB> __device__ __forceinline__ void wg_n256(float (&d)[128], uint32_t descA, uint32_t descB, int scaleD) {
  asm volatile("{\n.reg .pred p;\n.reg .b64 da, db;\n"
    "mov.b64 da, {%128, %131};\nmov.b64 db, {%129, %132};\n"
    "setp.ne.b32 p, %130, 0;\n"
    "wgmma.mma_async.sync.aligned.m64n256k16.f32.bf16.bf16 "
    "{%0, %1, %2, %3, %4, %5, %6, %7, %8, %9, %10, %11, %12, %13, %14, %15, "
    "%16, %17, %18, %19, %20, %21, %22, %23, %24, %25, %26, %27, %28, %29, %30, %31, "
    "%32, %33, %34, %35, %36, %37, %38, %39, %40, %41, %42, %43, %44, %45, %46, %47, "
    "%48, %49, %50, %51, %52, %53, %54, %55, %56, %57, %58, %59, %60, %61, %62, %63, "
    "%64, %65, %66, %67, %68, %69, %70, %71, %72, %73, %74, %75, %76, %77, %78, %79, "
    "%80, %81, %82, %83, %84, %85, %86, %87, %88, %89, %90, %91, %92, %93, %94, %95, "
    "%96, %97, %98, %99, %100, %101, %102, %103, %104, %105, %106, %107, %108, %109, %110, %111, "
    "%112, %113, %114, %115, %116, %117, %118, %119, %120, %121, %122, %123, %124, %125, %126, %127}, "
    "da, db, p, 1, 1, 0, 1;\n}\n"
    : "+f"(d[0]), "+f"(d[1]), "+f"(d[2]), "+f"(d[3]), "+f"(d[4]), "+f"(d[5]), "+f"(d[6]), "+f"(d[7]),
      "+f"(d[8]), "+f"(d[9]), "+f"(d[10]), "+f"(d[11]), "+f"(d[12]), "+f"(d[13]), "+f"(d[14]), "+f"(d[15]),
      "+f"(d[16]), "+f"(d[17]), "+f"(d[18]), "+f"(d[19]), "+f"(d[20]), "+f"(d[21]), "+f"(d[22]), "+f"(d[23]),
      "+f"(d[24]), "+f"(d[25]), "+f"(d[26]), "+f"(d[27]), "+f"(d[28]), "+f"(d[29]), "+f"(d[30]), "+f"(d[31]),
      "+f"(d[32]), "+f"(d[33]), "+f"(d[34]), "+f"(d[35]), "+f"(d[36]), "+f"(d[37]), "+f"(d[38]), "+f"(d[39]),
      "+f"(d[40]), "+f"(d[41]), "+f"(d[42]), "+f"(d[43]), "+f"(d[44]), "+f"(d[45]), "+f"(d[46]), "+f"(d[47]),
      "+f"(d[48]), "+f"(d[49]), "+f"(d[50]), "+f"(d[51]), "+f"(d[52]), "+f"(d[53]), "+f"(d[54]), "+f"(d[55]),
      "+f"(d[56]), "+f"(d[57]), "+f"(d[58]), "+f"(d[59]), "+f"(d[60]), "+f"(d[61]), "+f"(d[62]), "+f"(d[63]),
      "+f"(d[64]), "+f"(d[65]), "+f"(d[66]), "+f"(d[67]), "+f"(d[68]), "+f"(d[69]), "+f"(d[70]), "+f"(d[71]),
      "+f"(d[72]), "+f"(d[73]), "+f"(d[74]), "+f"(d[75]), "+f"(d[76]), "+f"(d[77]), "+f"(d[78]), "+f"(d[79]),
      "+f"(d[80]), "+f"(d[81]), "+f"(d[82]), "+f"(d[83]), "+f"(d[84]), "+f"(d[85]), "+f"(d[86]), "+f"(d[87]),
      "+f"(d[88]), "+f"(d[89]), "+f"(d[90]), "+f"(d[91]), "+f"(d[92]), "+f"(d[93]), "+f"(d[94]), "+f"(d[95]),
      "+f"(d[96]), "+f"(d[97]), "+f"(d[98]), "+f"(d[99]), "+f"(d[100]), "+f"(d[101]), "+f"(d[102]), "+f"(d[103]),
      "+f"(d[104]), "+f"(d[105]), "+f"(d[106]), "+f"(d[107]), "+f"(d[108]), "+f"(d[109]), "+f"(d[110]), "+f"(d[111]),
      "+f"(d[112]), "+f"(d[113]), "+f"(d[114]), "+f"(d[115]), "+f"(d[116]), "+f"(d[117]), "+f"(d[118]), "+f"(d[119]),
      "+f"(d[120]), "+f"(d[121]), "+f"(d[122]), "+f"(d[123]), "+f"(d[124]), "+f"(d[125]), "+f"(d[126]), "+f"(d[127])
    : "r"(descA), "r"(descB), "r"(scaleD), "n"(HA), "n"(HB));
}

namespace {

constexpr int S_ = 2048, D_ = 1024, F_ = 3584;
constexpr int NCTA = 128;
constexpr int NTHREADS = 384;

constexpr uint32_t W_OFF      = 6 * 16384;
constexpr uint32_t BAR_OFF    = W_OFF + 16 * 8192;
constexpr uint32_t PAR_OFF    = BAR_OFF + 1280;
constexpr uint32_t SMEM_BYTES = 232448, SMEM_BASE = 1024;
constexpr uint32_t SL_OFF     = W_OFF + 11 * 8192;
constexpr uint32_t TAB_OFF    = W_OFF + 15 * 8192;
constexpr uint32_t B_R = 1024, B_PAR = 1072, B_SL = 1120, B_SLE = 1088, B_Q = 1096, B_ST = 1152, B_GB = 1056, B_XB = 1168, B_END = 1184, ROLE_OFF = 1272;

constexpr uint32_t H128 = 0x40000040u;
constexpr uint32_t H64  = 0x80000020u;

constexpr int N_W = 137, N_HK = 3, N_END = 130;
__constant__ uint2 c_cons[2][135] = {
  {
    {0x0,0x84580800}, {0x6000400,0x84580808}, {0x18000800,0x84580810}, {0x12000c00,0x84580818}, {0xc001000,0x84580820}, {0x0,0x84580828},
    {0x6000400,0x84580830}, {0x18000800,0x84580838}, {0x12000c00,0x84580840}, {0xc000000,0x84580848}, {0x800,0x84580850}, {0x6000c00,0x84580858},
    {0x18000000,0x84580860}, {0x12000800,0x84580868}, {0xc000c00,0x84580870}, {0x0,0x84580878}, {0x400,0x84580880}, {0x400,0x84580888},
    {0x18001000,0x4500890}, {0x1c000000,0x84580898}, {0x14000800,0x845818a0}, {0xc001400,0x41008a8}, {0x10000c00,0x845818b0}, {0x1000,0x41808b8},
    {0x4000000,0x845808c0}, {0x8000800,0x845808c8}, {0x1400,0x845808d0}, {0x1400,0x845808d8}, {0x18000000,0x3b808e0}, {0xc000800,0x845808e8},
    {0x12001400,0x845808f0}, {0xc00,0x845808f8}, {0x6001000,0x84580c00}, {0x18000400,0x84580c08}, {0xc000000,0x84580c10}, {0x12000800,0x84580c18},
    {0xc00,0x84580c20}, {0x6000400,0x84580c28}, {0x18000800,0x84580c30}, {0xc000c00,0x84580c38}, {0x12000400,0x84580c40}, {0x800,0x84580c48},
    {0x6000c00,0x84580c50}, {0x18000400,0x84580c58}, {0x0,0x3d80c60}, {0x14001400,0x83500c68}, {0xc00,0x84580c70}, {0x4001000,0x84580c78},
    {0x8000400,0x84580c80}, {0x18000000,0x84580c88}, {0xc000800,0x84580c90}, {0x10000c00,0x84580c98}, {0x1c000400,0x84580ca0}, {0x14000800,0x84580ca8},
    {0xc00,0x84580cb0}, {0x4000400,0x84580cb8}, {0x8000800,0x84580cc0}, {0x18000c00,0x84580cc8}, {0xc000400,0x84580cd0}, {0x10000800,0x84580cd8},
    {0x1c000c00,0x84580ce0}, {0x14001000,0x83d80ce8}, {0x400,0x84580cf0}, {0x4000000,0x84580cf8}, {0x8000800,0x84580800}, {0x18001400,0x84580808},
    {0xc000c00,0x84580810}, {0x10000400,0x84580818}, {0x1c000800,0x84580820}, {0x14000c00,0x84580828}, {0x400,0x84580830}, {0x4000800,0x84580838},
    {0x8000c00,0x84580840}, {0x18000400,0x84580848}, {0xc000800,0x84580850}, {0x10000c00,0x84580858}, {0x1c000400,0x84580860}, {0x14000000,0x3580868},
    {0x800,0x84580870}, {0x4001400,0x84580878}, {0x8000c00,0x84580880}, {0x18001000,0x84580888}, {0xc000400,0x84580890}, {0x10000000,0x84580898},
    {0x1c000800,0x845808a0}, {0x14001400,0x845808a8}, {0xc00,0x845808b0}, {0x4001000,0x845808b8}, {0x8000400,0x845808c0}, {0x18000000,0x845808c8},
    {0xc000800,0x845808d0}, {0x10001400,0x845808d8}, {0x1c000c00,0x845808e0}, {0x14001000,0x845808e8}, {0x400,0x845808f0}, {0x4000000,0x845808f8},
    {0x8000800,0x84580c00}, {0x18001400,0x84580c08}, {0xc000c00,0x84580c10}, {0x10001000,0x84580c18}, {0x1c000400,0x84580c20}, {0x14000000,0x84580c28},
    {0x800,0x84580c30}, {0x4001400,0x84580c38}, {0x8000c00,0x84580c40}, {0x18001000,0x84580c48}, {0xc000400,0x84580c50}, {0x10000000,0x84580c58},
    {0x1c000800,0x84580c60}, {0x14001400,0x84580c68}, {0xc00,0x84580c70}, {0x4001000,0x84580c78}, {0x8000400,0x84580c80}, {0x18000000,0x84580c88},
    {0xc000800,0x84580c90}, {0x10001400,0x84580c98}, {0x1c000c00,0x84580ca0}, {0x14001000,0x84580ca8}, {0x400,0x84580cb0}, {0x4000000,0x84580cb8},
    {0x8000800,0x84580cc0}, {0x18001400,0x84580cc8}, {0xc000c00,0x84580cd0}, {0x10001000,0x84580cd8}, {0x1c000400,0x84580ce0}, {0x14000000,0x84580ce8},
    {0x800,0x84580cf0}, {0x4001400,0x84580cf8}, {0x8000c00,0x84580800}, {0x18001000,0x84580808}, {0x400,0x84580010}, {0x0,0x84580018},
    {0x14000800,0x0}, {0x14000800,0x0}, {0x14000800,0x0},
  },
  {
    {0x6001400,0x300900}, {0x18001000,0x380908}, {0x12000400,0x400910}, {0xc001400,0x480918}, {0x1000,0x500920}, {0x6000400,0x580928},
    {0x18001400,0x600930}, {0x12001000,0x680938}, {0xc000800,0x4480940}, {0x1400,0x84581948}, {0x6000c00,0x4001950}, {0x18001000,0x4080958},
    {0x12000000,0x84580960}, {0xc000800,0x84580968}, {0x1400,0x84580970}, {0x6000c00,0x84580978}, {0x400,0x84580980}, {0x400,0x84580988},
    {0x18000c00,0x2b80990}, {0x1c001000,0x84580998}, {0x14000400,0x845809a0}, {0xc000000,0x845809a8}, {0x10000800,0x845809b0}, {0x1400,0x845809b8},
    {0x4000c00,0xc009c0}, {0x8001000,0xc809c8}, {0x400,0x845809d0}, {0x400,0x845809d8}, {0xc001400,0x801009e0}, {0x12001000,0x801809e8},
    {0x0,0x802009f0}, {0x6001400,0x802809f8}, {0x18001000,0x80300d00}, {0xc000000,0x80380d08}, {0x12001400,0x80400d10}, {0x1000,0x80480d18},
    {0x6000000,0x82500d20}, {0x18000800,0x80580d28}, {0xc001400,0x84580d30}, {0x12000c00,0x84580d38}, {0x1000,0x84580d40}, {0x6000400,0x84580d48},
    {0x18000000,0x84580d50}, {0xc000800,0x84580d58}, {0x0,0x82600d60}, {0x14001400,0x82680d68}, {0x1000,0x82700d70}, {0x4000000,0x82780d78},
    {0x8001400,0x82800d80}, {0x18001000,0x82880d88}, {0xc000000,0x82900d90}, {0x10001400,0x82980d98}, {0x1c001000,0x82a00da0}, {0x14000000,0x82a80da8},
    {0x1400,0x82b00db0}, {0x4001000,0x82d80db8}, {0x8000400,0x84580dc0}, {0x18000000,0x84580dc8}, {0xc000800,0x84580dd0}, {0x10001400,0x84580dd8},
    {0x1c000c00,0x82e00de0}, {0x14001000,0x82e80de8}, {0x0,0x82f00df0}, {0x4001400,0x82f80df8}, {0x8001000,0x2000900}, {0x18000000,0x2080908},
    {0xc001400,0x2100910}, {0x10001000,0x2180918}, {0x1c000000,0x2200920}, {0x14001400,0x2280928}, {0x1000,0x2300930}, {0x4000000,0x2580938},
    {0x8000800,0x84580940}, {0x18001400,0x84580948}, {0xc000c00,0x84580950}, {0x10001000,0x84580958}, {0x1c000400,0x2600960}, {0x14000000,0x2680968},
    {0x800,0x2700970}, {0x4001400,0x2780978}, {0x8000c00,0x2800980}, {0x18001000,0x2880988}, {0xc000400,0x2900990}, {0x10000000,0x2980998},
    {0x1c000800,0x2a009a0}, {0x14001400,0x2a809a8}, {0xc00,0x2b009b0}, {0x4001000,0x2b809b8}, {0x8000400,0x2c009c0}, {0x18000000,0x2c809c8},
    {0xc000800,0x2d009d0}, {0x10001400,0x2d809d8}, {0x1c000c00,0x2e009e0}, {0x14001000,0x2e809e8}, {0x400,0x2f009f0}, {0x4000000,0x2f809f8},
    {0x8000800,0x82000d00}, {0x18001400,0x82080d08}, {0xc000c00,0x82100d10}, {0x10001000,0x82180d18}, {0x1c000400,0x82200d20}, {0x14000000,0x82280d28},
    {0x800,0x82300d30}, {0x4001400,0x82380d38}, {0x8000c00,0x82400d40}, {0x18001000,0x82480d48}, {0xc000400,0x82500d50}, {0x10000000,0x82580d58},
    {0x1c000800,0x82600d60}, {0x14001400,0x82680d68}, {0xc00,0x82700d70}, {0x4001000,0x82780d78}, {0x8000400,0x82800d80}, {0x18000000,0x82880d88},
    {0xc000800,0x82900d90}, {0x10001400,0x82980d98}, {0x1c000c00,0x82a00da0}, {0x14001000,0x82a80da8}, {0x400,0x82b00db0}, {0x4000000,0x82b80db8},
    {0x8000800,0x82c00dc0}, {0x18001400,0x82c80dc8}, {0xc000c00,0x82d00dd0}, {0x10001000,0x82d80dd8}, {0x1c000400,0x82e00de0}, {0x14000000,0x82e80de8},
    {0x800,0x20005f0}, {0x4001400,0x845805f8}, {0x8000c00,0x84580100}, {0x18001000,0x2080108}, {0x400,0x84580110}, {0x0,0x84580118},
    {0x14000800,0x0}, {0x14000800,0x0}, {0x14000800,0x0},
  },
};
__constant__ uint2 c_act[2][135] = {
  {
    {0x81000458,0xa0000000}, {0x80004458,0xa0004008}, {0x80008458,0xa0008010}, {0x8000c458,0xa000c018}, {0x80010458,0xa0010020}, {0x14200,0xa0000028},
    {0x18208,0xa0004030}, {0x1c210,0xa0008038}, {0x3020218,0xa000c040}, {0x24228,0xa0000048}, {0x28238,0xa0008050}, {0x2c240,0xa000c058},
    {0x30248,0xa0000060}, {0x34250,0xa0008068}, {0x38258,0xa000c070}, {0x3c260,0xa0000078}, {0x328,0x4080}, {0x280,0x40004088},
    {0x5080358,0x80010090}, {0x88360,0x80000098}, {0x90368,0x800080a0}, {0x98370,0x800140a8}, {0xa0378,0x8000c0b0}, {0xa8290,0x800100b8},
    {0xb0298,0x800000c0}, {0xb82a0,0x800080c8}, {0x2a8,0x140d0}, {0x80000458,0x400140d8}, {0x70003a8,0xa00000e0}, {0x43b0,0xa00080e8},
    {0x83b8,0xa00140f0}, {0xc3c0,0xa000c0f8}, {0x103c8,0xa0010000}, {0x143d8,0xa0004008}, {0x182e0,0xa0000010}, {0x1c2e8,0xa0008018},
    {0x202f8,0xa000c020}, {0x80024208,0xa0004028}, {0x80028218,0xa0008030}, {0x8002c220,0xa000c038}, {0x80030228,0xa0004040}, {0x80034230,0xa0008048},
    {0x80038238,0xa000c050}, {0x8003c240,0xa0004058}, {0x80000458,0x20000060}, {0x80000330,0x80014068}, {0x80004338,0x8000c070}, {0x80008340,0x80010078},
    {0x8000c348,0x80004080}, {0x80010350,0x80000088}, {0x80014358,0x80008090}, {0x80018270,0x8000c098}, {0x8001c280,0x800040a0}, {0x80020290,0x800080a8},
    {0x80024298,0x8000c0b0}, {0x800282a0,0x800040b8}, {0x8002c2a8,0x800080c0}, {0x800302b0,0x8000c0c8}, {0x800342b8,0x800040d0}, {0x800382c0,0x800080d8},
    {0x8003c2c8,0x8000c0e0}, {0x800003b8,0x800100e8}, {0x800043c0,0x800040f0}, {0x800083c8,0x800000f8}, {0x8000c3d0,0x80008000}, {0x800103d8,0x80014008},
    {0x800143e0,0x8000c010}, {0x800182f0,0x80004018}, {0x1c200,0x80008020}, {0x20210,0x8000c028}, {0x24218,0x80004030}, {0x28220,0x80008038},
    {0x2c228,0x8000c040}, {0x30230,0x80004048}, {0x34238,0x80008050}, {0x38240,0x8000c058}, {0x3c248,0x80004060}, {0x918c338,0x60000068},
    {0x190340,0x60008070}, {0x194348,0x60014078}, {0x198350,0x6000c080}, {0x19c358,0x60010088}, {0x1a0360,0x60004090}, {0x1a4268,0x60000098},
    {0x1a8270,0x600080a0}, {0x1ac278,0x600140a8}, {0x1b0280,0x6000c0b0}, {0x1b4288,0x600100b8}, {0x1b8290,0x600040c0}, {0x1bc298,0x600000c8},
    {0x1c02a0,0x600080d0}, {0x1c42a8,0x600140d8}, {0x1c82b0,0x6000c0e0}, {0x1cc2b8,0x600100e8}, {0x1d02c0,0x600040f0}, {0x1d42c8,0x600000f8},
    {0x1d82d0,0x60008000}, {0x1dc2d8,0x60014008}, {0xb1e02e0,0x6000c010}, {0x1e42e8,0x60010018}, {0x1e82f0,0x60004020}, {0x1ec2f8,0x60000028},
    {0x801f0200,0x60008030}, {0x801f4208,0x60014038}, {0x801f8210,0x6000c040}, {0x801fc218,0x60010048}, {0x80200220,0x60004050}, {0x80204228,0x60000058},
    {0x80208230,0x60008060}, {0x8020c238,0x60014068}, {0x80210240,0x6000c070}, {0x80214248,0x60010078}, {0x80218250,0x60004080}, {0x8021c258,0x60000088},
    {0x8d220260,0x60008090}, {0x80224268,0x60014098}, {0x80228270,0x6000c0a0}, {0x8022c278,0x600100a8}, {0x80230280,0x600040b0}, {0x80234288,0x600000b8},
    {0x80238290,0x600080c0}, {0x8023c298,0x600140c8}, {0x802402a0,0x6000c0d0}, {0x802442a8,0x600100d8}, {0x802482b0,0x600040e0}, {0x8024c2b8,0x600000e8},
    {0x802502c0,0x600080f0}, {0x802542c8,0x600140f8}, {0x802582d0,0x6000c000}, {0x8025c2d8,0x60010008}, {0x801002e0,0x20004010}, {0x801042e8,0x20000018},
    {0x0,0x0}, {0x0,0x0}, {0x0,0x0},
  },
  {
    {0x91058458,0x40014100}, {0x5c220,0x40010108}, {0x60230,0x40004110}, {0x64300,0x40014118}, {0x68308,0x40010120}, {0x6c310,0x40004128},
    {0x70318,0x40014130}, {0x74320,0x40010138}, {0x78268,0x40008140}, {0x7c330,0x40014148}, {0x40270,0xa000c150}, {0x44338,0xa0010158},
    {0x48278,0xa0000160}, {0x4c340,0xa0008168}, {0x50348,0xa0014170}, {0x54350,0xa000c178}, {0x288,0x4180}, {0x380,0x40004188},
    {0x150c02b0,0x4000c190}, {0xc82b8,0x40010198}, {0xd0388,0x400041a0}, {0xd82c0,0x400001a8}, {0xe02c8,0x400081b0}, {0xe82d8,0x400141b8},
    {0xf0390,0x4000c1c0}, {0xf8398,0x400101c8}, {0x3a0,0x41d0}, {0x80000458,0x400041d8}, {0x170582f0,0x400141e0}, {0x8005c200,0x400101e8},
    {0x80060210,0x400001f0}, {0x643e0,0x400141f8}, {0x683e8,0x40010100}, {0x6c3f0,0x40000108}, {0x703f8,0x40014110}, {0x80074300,0x40010118},
    {0x80078308,0x40000120}, {0x8007c248,0x40008128}, {0x80040310,0xa0014130}, {0x80044250,0xa000c138}, {0x80048318,0xa0010140}, {0x8004c258,0xa0004148},
    {0x80050320,0xa0000150}, {0x80054328,0xa0008158}, {0x80000458,0x20000160}, {0x80040268,0x40014168}, {0x80044278,0x40010170}, {0x80048288,0x40000178},
    {0x8004c368,0x40014180}, {0x80050370,0x40010188}, {0x80054378,0x40000190}, {0x80058380,0x40014198}, {0x8005c388,0x400101a0}, {0x80060390,0x400001a8},
    {0x80064398,0x400141b0}, {0x800683a0,0x400101b8}, {0x8006c2d0,0x400041c0}, {0x800703a8,0x400001c8}, {0x800742d8,0x400081d0}, {0x800783b0,0x400141d8},
    {0x8007c2e0,0x4000c1e0}, {0x800402e8,0x400101e8}, {0x800442f8,0x400001f0}, {0x48208,0x400141f8}, {0x8004c3e8,0x40010100}, {0x800503f0,0x40000108},
    {0x800543f8,0x40014110}, {0x58300,0x40010118}, {0x5c308,0x40000120}, {0x60310,0x40014128}, {0x64318,0x40010130}, {0x68320,0x40000138},
    {0x6c250,0x40008140}, {0x70328,0x40014148}, {0x74258,0x4000c150}, {0x78330,0x40010158}, {0x7c260,0x40004160}, {0x918c338,0x20000168},
    {0x190340,0x20008170}, {0x194348,0x20014178}, {0x198350,0x2000c180}, {0x19c358,0x20010188}, {0x1a0360,0x20004190}, {0x1a4368,0x20000198},
    {0x1a8370,0x200081a0}, {0x1ac378,0x200141a8}, {0x1b0380,0x2000c1b0}, {0x1b4388,0x200101b8}, {0x1b8390,0x200041c0}, {0x1bc398,0x200001c8},
    {0x1c03a0,0x200081d0}, {0x1c43a8,0x200141d8}, {0x1c83b0,0x2000c1e0}, {0x1cc3b8,0x200101e8}, {0x1d03c0,0x200041f0}, {0x1d43c8,0x200001f8},
    {0x1d83d0,0x20008100}, {0x1dc3d8,0x20014108}, {0xb1e03e0,0x2000c110}, {0x1e43e8,0x20010118}, {0x1e83f0,0x20004120}, {0x1ec3f8,0x20000128},
    {0x801f0300,0x20008130}, {0x801f4308,0x20014138}, {0x801f8310,0x2000c140}, {0x801fc318,0x20010148}, {0x80200320,0x20004150}, {0x80204328,0x20000158},
    {0x80208330,0x20008160}, {0x8020c338,0x20014168}, {0x80210340,0x2000c170}, {0x80214348,0x20010178}, {0x80218350,0x20004180}, {0x8021c358,0x20000188},
    {0x8d220360,0x20008190}, {0x80224368,0x20014198}, {0x80228370,0x2000c1a0}, {0x8022c378,0x200101a8}, {0x80230380,0x200041b0}, {0x80234388,0x200001b8},
    {0x80238390,0x200081c0}, {0x8023c398,0x200141c8}, {0x802403a0,0x2000c1d0}, {0x802443a8,0x200101d8}, {0x802483b0,0x200041e0}, {0x8024c3b8,0x200001e8},
    {0x802503c0,0x200081f0}, {0x802543c8,0x200141f8}, {0x802583d0,0x2000c100}, {0x8025c3d8,0x20010108}, {0x801003e0,0x20004110}, {0x801043e8,0x20000118},
    {0x0,0x0}, {0x0,0x0}, {0x0,0x0},
  },
};
__constant__ uint2 c_w[1][138] = {
  {
    {0x84580000,0x20000}, {0x84580000,0x2026008}, {0x84580000,0x4038010}, {0x84580000,0x6032018}, {0x84580000,0x802c020}, {0x2000000,0xa000028},
    {0x2080000,0xc006030}, {0x2100000,0xe018038}, {0x2180000,0x10012040}, {0x2200000,0x1200c048}, {0x2280000,0x14000050}, {0x2300300,0x16006058},
    {0x2380308,0x18018060}, {0x2400310,0x1a012068}, {0x2480318,0x1c00c070}, {0x2500320,0x1e000078}, {0x2580328,0x6150}, {0x2600330,0x2018158},
    {0x2680338,0x4012160}, {0x2700340,0x600c168}, {0x2780348,0x8000170}, {0x3500000,0xa026178}, {0x3580000,0x18890}, {0x84580000,0x401c898},
    {0x3600000,0x80148a0}, {0x3680000,0xc00c8a8}, {0x84580000,0x100108b0}, {0x3700000,0x140008b8}, {0x3780000,0x180048c0}, {0x84580000,0x1c0288c8},
    {0x3980000,0x184e0}, {0x3b00000,0x200c4e8}, {0x84580000,0x40124f0}, {0x2c003c0,0x60004f8}, {0x2c803c8,0x8006400}, {0x2e00000,0xa018408},
    {0x2e80000,0xc00c410}, {0x2f00000,0xe012418}, {0x2f80000,0x10000420}, {0x82000000,0x12006428}, {0x82080000,0x14018430}, {0x821003e0,0x1600c438},
    {0x821803e8,0x18012440}, {0x822003f0,0x1a000448}, {0x822803f8,0x1c006450}, {0x82308300,0x1e018458}, {0x82388308,0xc530}, {0x82408310,0x2012538},
    {0x82488318,0x4000540}, {0x83200000,0x6006548}, {0x82588328,0x8018550}, {0x83300000,0xa02c558}, {0x83380000,0x14c68}, {0x83400000,0x2000c70},
    {0x83480000,0x4004c78}, {0x84580000,0x6008c80}, {0x83500000,0x8018c88}, {0x83580000,0xa00cc90}, {0x84580000,0xc010c98}, {0x83600000,0xe01cca0},
    {0x83680000,0x10014ca8}, {0x83700000,0x12000cb0}, {0x83780000,0x14004cb8}, {0x83800000,0x16008cc0}, {0x83880000,0x18018cc8}, {0x83900000,0x1a00ccd0},
    {0x83980000,0x1c010cd8}, {0x83a00000,0x1e03cce0}, {0x83a80000,0x150e8}, {0x83b00000,0x20010f0}, {0x83b80000,0x40050f8}, {0x83c00000,0x6009000},
    {0x83c80000,0x8019008}, {0x83d00000,0xa00d010}, {0x83d80000,0xc011018}, {0x83e00000,0xe01d020}, {0x83e80000,0x10015028}, {0x83f00000,0x12001030},
    {0x83f80000,0x14005038}, {0x3000000,0x16009040}, {0x3080000,0x18019048}, {0x3100000,0x1a00d050}, {0x3180000,0x1c011058}, {0x3200000,0x1e03d060},
    {0x3280000,0x6015468}, {0x3300000,0x8001470}, {0x3380000,0xa005478}, {0x3400000,0xc009480}, {0x3480000,0xe019488}, {0x3500000,0x1000d490},
    {0x3580000,0x12011498}, {0x3600000,0x1401d4a0}, {0x3680000,0x160154a8}, {0x3700000,0x180014b0}, {0x3780000,0x1a0054b8}, {0x3800000,0x1c0094c0},
    {0x3880000,0x1e0194c8}, {0x3900000,0x2000d4d0}, {0x3980000,0x220114d8}, {0x3a00000,0x2401d4e0}, {0x3a80000,0x260154e8}, {0x3b00000,0x280014f0},
    {0x3b80000,0x2a0054f8}, {0x3c00000,0x2c009400}, {0x3c80000,0x2e019408}, {0x3d00000,0x3000d410}, {0x3d80000,0x32011418}, {0x3e00000,0x3401d420},
    {0x3e80000,0x36015428}, {0x3f00000,0x38001430}, {0x3f80000,0x3a005438}, {0x83000000,0x3c009440}, {0x83080000,0x3e019448}, {0x83100000,0x4000d450},
    {0x83180000,0x42011458}, {0x83200000,0x4401d460}, {0x83280000,0x46015468}, {0x83300000,0x48001470}, {0x83380000,0x4a005478}, {0x83400000,0x4c009480},
    {0x83480000,0x4e019488}, {0x83500000,0x5000d490}, {0x83580000,0x52011498}, {0x83600000,0x5401d4a0}, {0x83680000,0x560154a8}, {0x83700000,0x580014b0},
    {0x83780000,0x5a0054b8}, {0x83800000,0x5c0094c0}, {0x83880000,0x5e0194c8}, {0x83900000,0x6000d4d0}, {0x83980000,0x620114d8}, {0x83a00000,0x6401d4e0},
    {0x83a80000,0x660154e8}, {0x83b00000,0x680014f0}, {0x83b80000,0x6a0054f8}, {0x83c00000,0x6c009400}, {0x83c80000,0x6e039408}, {0x0,0x0},
  },
};

constexpr int T_H = 0, T_O = 32, T_X1 = 64, T_ACT = 96, N_TILES = 208;
constexpr int G_H0 = 0, G_H1 = 1, G_O = 2, G_H2 = 3, G_ACT = 4, G_X1 = 7, G_HK = 15;

struct Scratch {
  uint4 img[8 * N_TILES * 1024];
  uint32_t mod0[4 * 4 * 512];
  uint32_t modp[4096];
  uint2 stat[32 * 8 * 64];
  uint4 halo[16 * 16 * 128];
  uint32_t cnt[8 * 32];
  uint32_t ep[(NCTA + 4) * 32];
};
__device__ __align__(1024) Scratch g_s;

struct Ptrs {
  const __nv_bfloat16 *x, *c;
  Scratch* s;
  __nv_bfloat16* out;
};
struct Params {
  CUtensorMap mWqkv, mWo, mWg, mWu, mWd, mOut, mWm2, mX;
};

__device__ __forceinline__ uint32_t smem_u32(const void* p) { return (uint32_t)__cvta_generic_to_shared(p); }
__device__ __forceinline__ void mbar_init(uint32_t bar, uint32_t cnt) { asm volatile("mbarrier.init.shared::cta.b64 [%0], %1;" ::"r"(bar), "r"(cnt)); }
__device__ __forceinline__ void mbar_expect_tx(uint32_t bar, uint32_t bytes) { asm volatile("mbarrier.arrive.expect_tx.shared::cta.b64 _, [%0], %1;" ::"r"(bar), "r"(bytes) : "memory"); }
__device__ __forceinline__ void mbar_arrive(uint32_t bar) { asm volatile("mbarrier.arrive.shared::cta.b64 _, [%0];" ::"r"(bar) : "memory"); }
__device__ __forceinline__ void mbar_arrive_remote(uint32_t bar_cluster) { asm volatile("mbarrier.arrive.shared::cluster.b64 _, [%0];" ::"r"(bar_cluster) : "memory"); }
__device__ __forceinline__ uint32_t mapa(uint32_t a, uint32_t cta) { uint32_t r; asm volatile("mapa.shared::cluster.u32 %0, %1, %2;" : "=r"(r) : "r"(a), "r"(cta)); return r; }
__device__ __forceinline__ void mbar_wait(uint32_t bar, uint32_t parity) {
  asm volatile("{\n.reg .pred p;\nW: mbarrier.try_wait.parity.shared::cta.b64 p, [%0], %1;\n@!p bra W;\n}" ::"r"(bar), "r"(parity) : "memory");
}
__device__ __forceinline__ void mbar_wait_bounded(uint32_t bar, uint32_t parity) {
  asm volatile("{\n.reg .pred p;\n.reg .u32 c;\nmov.u32 c, 0;\n"
               "W: mbarrier.try_wait.parity.shared::cta.b64 p, [%0], %1;\n@p bra D;\n"
               "add.u32 c, c, 1;\nsetp.lt.u32 p, c, 0x200000;\n@p bra W;\ntrap;\nD:\n}" ::"r"(bar), "r"(parity) : "memory");
}
constexpr uint32_t POLL_MAX = 1u << 20;
__device__ __forceinline__ void guard(uint32_t it) { asm volatile("{\n.reg .pred p;\nsetp.gt.u32 p, %0, 0x100000;\n@p trap;\n}" ::"r"(it)); }
__device__ __forceinline__ bool mbar_test(uint32_t bar, uint32_t parity) {
  uint32_t p; asm volatile("{\n.reg .pred P;\nmbarrier.test_wait.parity.shared::cta.b64 P, [%1], %2;\nselp.u32 %0, 1, 0, P;\n}" : "=r"(p) : "r"(bar), "r"(parity) : "memory"); return p;
}
__device__ __forceinline__ bool elect_one() {
  uint32_t p; asm volatile("{\n.reg .pred P;\nelect.sync _|P, 0xffffffff;\nselp.u32 %0, 1, 0, P;\n}" : "=r"(p)); return p;
}
__device__ __forceinline__ bool only_one() { asm volatile("{\n.reg .pred P;\nelect.sync _|P, 0xffffffff;\n@!P exit;\n}" ::: "memory"); return true; }
__device__ __forceinline__ void tma2d(uint32_t dst, const CUtensorMap* m, uint32_t bar, int c0, int c1) {
  asm volatile("cp.async.bulk.tensor.2d.shared::cluster.global.mbarrier::complete_tx::bytes [%0], [%1, {%3, %4}], [%2];" ::"r"(dst), "l"(m), "r"(bar), "r"(c0), "r"(c1) : "memory");
}
__device__ __forceinline__ uint64_t evict_first() { uint64_t p; asm("createpolicy.fractional.L2::evict_first.b64 %0, 1.0;" : "=l"(p)); return p; }
__device__ __forceinline__ void tma2d_once(uint32_t dst, const CUtensorMap* m, uint32_t bar, int c0, int c1) {
  asm volatile("cp.async.bulk.tensor.2d.shared::cluster.global.mbarrier::complete_tx::bytes.L2::cache_hint [%0], [%1, {%3, %4}], [%2], %5;" ::"r"(dst), "l"(m), "r"(bar), "r"(c0), "r"(c1), "l"(evict_first()) : "memory");
}
__device__ __forceinline__ void tma5d_once(uint32_t dst, const CUtensorMap* m, uint32_t bar, int c0, int c4) {
  asm volatile("cp.async.bulk.tensor.5d.shared::cluster.global.mbarrier::complete_tx::bytes.L2::cache_hint [%0], [%1, {%3, %5, %5, %5, %4}], [%2], %6;" ::"r"(dst), "l"(m), "r"(bar), "r"(c0), "r"(c4), "r"(0), "l"(evict_first()) : "memory");
}
__device__ __forceinline__ void tma5d(uint32_t dst, const CUtensorMap* m, uint32_t bar, int c0, int c4) {
  asm volatile("cp.async.bulk.tensor.5d.shared::cluster.global.mbarrier::complete_tx::bytes [%0], [%1, {%3, %5, %5, %5, %4}], [%2];" ::"r"(dst), "l"(m), "r"(bar), "r"(c0), "r"(c4), "r"(0) : "memory");
}
__device__ __forceinline__ void tma2d_st(const CUtensorMap* m, uint32_t src, int c0, int c1) {
  asm volatile("cp.async.bulk.tensor.2d.global.shared::cta.bulk_group [%0, {%2, %3}], [%1];" ::"l"(m), "r"(src), "r"(c0), "r"(c1) : "memory");
}
__device__ __forceinline__ void bulk_g2s(uint32_t dst, const void* src, uint32_t bytes, uint32_t bar) {
  asm volatile("cp.async.bulk.shared::cluster.global.mbarrier::complete_tx::bytes [%0], [%1], %2, [%3];" ::"r"(dst), "l"(src), "r"(bytes), "r"(bar) : "memory");
}
__device__ __forceinline__ void bulk_g2s_mc(uint32_t dst, const void* src, uint32_t bytes, uint32_t bar) {
  asm volatile("cp.async.bulk.shared::cluster.global.mbarrier::complete_tx::bytes.multicast::cluster [%0], [%1], %2, [%3], %4;" ::"r"(dst), "l"(src), "r"(bytes), "r"(bar), "h"((uint16_t)3) : "memory");
}
__device__ __forceinline__ void st_async(uint32_t dst, uint32_t bar, uint32_t a, uint32_t b, uint32_t c, uint32_t d) {
  asm volatile("st.async.weak.shared::cluster.mbarrier::complete_tx::bytes.v4.b32 [%0], {%2,%3,%4,%5}, [%1];" ::"r"(dst), "r"(bar), "r"(a), "r"(b), "r"(c), "r"(d) : "memory");
}
__device__ __forceinline__ void bulk_commit() { asm volatile("cp.async.bulk.commit_group;" ::: "memory"); }
__device__ __forceinline__ void bulk_wait_read() { asm volatile("cp.async.bulk.wait_group.read 0;" ::: "memory"); }
__device__ __forceinline__ void fence_async_smem() { asm volatile("fence.proxy.async.shared::cta;" ::: "memory"); }
__device__ __forceinline__ void fence_async_glob() { asm volatile("fence.proxy.async.global;" ::: "memory"); }
__device__ __forceinline__ void prefetch_tmap(const CUtensorMap* m) { asm volatile("prefetch.tensormap [%0];" ::"l"(m) : "memory"); }
__device__ __forceinline__ void wg_fence() { asm volatile("wgmma.fence.sync.aligned;" ::: "memory"); }
__device__ __forceinline__ void wg_commit() { asm volatile("wgmma.commit_group.sync.aligned;" ::: "memory"); }
template <int N> __device__ __forceinline__ void wg_wait() { asm volatile("wgmma.wait_group.sync.aligned %0;" ::"n"(N) : "memory"); }
template <int N> __device__ __forceinline__ void fence_regs(float (&a)[N]) {
#pragma unroll
  for (int i = 0; i < N; i++) asm volatile("" : "+f"(a[i])::"memory");
}
__device__ __forceinline__ uint32_t make_desc(uint32_t addr, uint32_t lbo) { return ((addr & 0x3FFFF) >> 4) | ((lbo >> 4) << 16); }
__device__ __forceinline__ void named_sync(int id, int n) { asm volatile("bar.sync %0, %1;" ::"r"(id), "r"(n) : "memory"); }
__device__ __forceinline__ uint32_t ld_relaxed(const void* p) { uint32_t v; asm volatile("ld.relaxed.gpu.global.u32 %0, [%1];" : "=r"(v) : "l"(p) : "memory"); return v; }
__device__ __forceinline__ uint32_t ld_relaxed_line(const void* p) { uint32_t v; asm volatile("ld.relaxed.gpu.global.L2::128B.u32 %0, [%1];" : "=r"(v) : "l"(p) : "memory"); return v; }
__device__ __forceinline__ void red_relaxed(uint32_t* p, uint32_t v) { asm volatile("red.relaxed.gpu.global.add.u32 [%0], %1;" ::"l"(p), "r"(v) : "memory"); }
__device__ __forceinline__ void st_relaxed(uint32_t* p, uint32_t v) { asm volatile("st.relaxed.gpu.global.u32 [%0], %1;" ::"l"(p), "r"(v) : "memory"); }
__device__ __forceinline__ uint2 ld_relaxed_b64(const uint2* p) {
  uint64_t a; asm volatile("ld.relaxed.gpu.global.b64 %0, [%1];" : "=l"(a) : "l"(p) : "memory");
  return make_uint2((uint32_t)a, (uint32_t)(a >> 32));
}
__device__ __forceinline__ void st_relaxed_b64(void* p, uint32_t lo, uint32_t hi) {
  uint64_t v = ((uint64_t)hi << 32) | lo;
  asm volatile("st.relaxed.gpu.global.b64 [%0], %1;" ::"l"(p), "l"(v) : "memory");
}
__device__ __forceinline__ void st_relaxed_v4(uint4* p, uint32_t a, uint32_t b, uint32_t c, uint32_t d) {
  asm volatile("st.relaxed.gpu.global.v4.u32 [%0], {%1,%2,%3,%4};" ::"l"(p), "r"(a), "r"(b), "r"(c), "r"(d) : "memory");
}
__device__ __forceinline__ bool empty(const uint4& v) { return v.x == ~0u || v.y == ~0u || v.z == ~0u || v.w == ~0u; }
__device__ __forceinline__ uint32_t tag_of(uint32_t ep) { return ep % 3 + 1; }
__device__ __forceinline__ uint32_t tagf(float v, uint32_t ep) {
  uint32_t r; asm volatile("lop3.b32 %0, %1, %2, 3, 0xD8;" : "=r"(r) : "r"(__float_as_uint(v)), "r"(ep)); return r;
}
__device__ __forceinline__ uint32_t tag_bad(const uint4& v, uint32_t ep) { return ((v.x ^ ep) | (v.y ^ ep) | (v.z ^ ep) | (v.w ^ ep)) & 3u; }
__device__ __forceinline__ uint4 ld_relaxed_v4(const void* p) {
  uint4 v; asm volatile("ld.relaxed.gpu.global.v4.u32 {%0,%1,%2,%3}, [%4];" : "=r"(v.x), "=r"(v.y), "=r"(v.z), "=r"(v.w) : "l"(p) : "memory"); return v;
}
__device__ __forceinline__ uint32_t ldg32(const void* p) { uint32_t v; asm volatile("ld.global.u32 %0, [%1];" : "=r"(v) : "l"(p) : "memory"); return v; }
__device__ __forceinline__ void stg128(uint4* p, uint32_t a, uint32_t b, uint32_t c, uint32_t d) {
  asm volatile("st.global.v4.b32 [%0], {%1,%2,%3,%4};" ::"l"(p), "r"(a), "r"(b), "r"(c), "r"(d) : "memory");
}
__device__ __forceinline__ void landed(uint32_t v) { if (__all_sync(~0u, v == 0xffffffffu)) __nanosleep(1); }
__device__ __forceinline__ void publish(uint32_t seen, uint32_t* cnt, uint32_t inc) {
  landed(seen);
  if (elect_one()) red_relaxed(cnt, inc);
}
__device__ __forceinline__ uint32_t pack_bf16(float lo, float hi) { uint32_t r; asm("cvt.rn.bf16x2.f32 %0, %1, %2;" : "=r"(r) : "f"(hi), "f"(lo)); return r; }
__device__ __forceinline__ float bf_lo(uint32_t v) { return __uint_as_float(v << 16); }
__device__ __forceinline__ float bf_hi(uint32_t v) { return __uint_as_float(v & 0xffff0000u); }
__device__ __forceinline__ uint32_t hmul2_bf16(uint32_t a, uint32_t b) { uint32_t r; asm("mul.rn.bf16x2 %0, %1, %2;" : "=r"(r) : "r"(a), "r"(b)); return r; }
__device__ __forceinline__ uint32_t hadd2_bf16(uint32_t a, uint32_t b) { uint32_t r; asm("add.rn.bf16x2 %0, %1, %2;" : "=r"(r) : "r"(a), "r"(b)); return r; }
__device__ __forceinline__ uint32_t hfma2_bf16(uint32_t a, uint32_t b, uint32_t c) { uint32_t r; asm("fma.rn.bf16x2 %0, %1, %2, %3;" : "=r"(r) : "r"(a), "r"(b), "r"(c)); return r; }
__device__ __forceinline__ void wgmma_n8(float (&d)[4], uint32_t descA, uint32_t descB, int scaleD) {
  asm volatile("{\n.reg .pred p;\n.reg .b64 da, db;\nmov.b64 da, {%4, 0x40000040};\nmov.b64 db, {%5, 0x40000040};\nsetp.ne.b32 p, %6, 0;\n"
               "wgmma.mma_async.sync.aligned.m64n8k16.f32.bf16.bf16 {%0,%1,%2,%3}, da, db, p, 1, 1, 1, 0;\n}\n"
               : "+f"(d[0]), "+f"(d[1]), "+f"(d[2]), "+f"(d[3]) : "r"(descA), "r"(descB), "r"(scaleD));
}
__device__ __forceinline__ float ex2(float x) { float r; asm("ex2.approx.ftz.f32 %0, %1;" : "=f"(r) : "f"(x)); return r; }
__device__ __forceinline__ float rcp(float x) { float r; asm("rcp.approx.ftz.f32 %0, %1;" : "=f"(r) : "f"(x)); return r; }
__device__ __forceinline__ float silu_f(float x) { return x * rcp(1.f + ex2(x * -1.4426950408889634f)); }
__device__ __forceinline__ float swiglu(float h, float hu) {
  float t; asm("tanh.approx.f32 %0, %1;" : "=f"(t) : "f"(h));
  return fmaf(hu, t, hu);
}
__device__ __forceinline__ void ldsm4(uint32_t addr, uint32_t& a, uint32_t& b, uint32_t& c, uint32_t& d) {
  asm volatile("ldmatrix.sync.aligned.m8n8.x4.shared.b16 {%0,%1,%2,%3}, [%4];" : "=r"(a), "=r"(b), "=r"(c), "=r"(d) : "r"(addr) : "memory");
}
__device__ __forceinline__ void stsm4(uint32_t addr, uint32_t a, uint32_t b, uint32_t c, uint32_t d) {
  asm volatile("stmatrix.sync.aligned.m8n8.x4.shared.b16 [%0], {%1,%2,%3,%4};" ::"r"(addr), "r"(a), "r"(b), "r"(c), "r"(d) : "memory");
}
__device__ __forceinline__ void sts128(uint32_t addr, uint32_t a, uint32_t b, uint32_t c, uint32_t d) {
  asm volatile("st.shared.v4.b32 [%0], {%1,%2,%3,%4};" ::"r"(addr), "r"(a), "r"(b), "r"(c), "r"(d) : "memory");
}
__device__ __forceinline__ void sts64(uint32_t addr, uint32_t a, uint32_t b) { asm volatile("st.shared.v2.b32 [%0], {%1,%2};" ::"r"(addr), "r"(a), "r"(b) : "memory"); }
__device__ __forceinline__ void sts32(uint32_t addr, uint32_t a) { asm volatile("st.shared.b32 [%0], %1;" ::"r"(addr), "r"(a) : "memory"); }
__device__ __forceinline__ uint4 lds128(uint32_t addr) {
  uint4 v; asm volatile("ld.shared.v4.b32 {%0,%1,%2,%3}, [%4];" : "=r"(v.x), "=r"(v.y), "=r"(v.z), "=r"(v.w) : "r"(addr) : "memory"); return v;
}
__device__ __forceinline__ uint32_t lds32(uint32_t addr) { uint32_t v; asm volatile("ld.shared.b32 %0, [%1];" : "=r"(v) : "r"(addr) : "memory"); return v; }
__device__ __forceinline__ uint32_t movm(uint32_t a) { uint32_t d; asm volatile("movmatrix.sync.aligned.m8n8.trans.b16 %0, %1;" : "=r"(d) : "r"(a)); return d; }
__device__ __forceinline__ void mma16816(float (&c)[4], uint32_t a0, uint32_t a1, uint32_t a2, uint32_t a3, uint32_t b0, uint32_t b1) {
  asm volatile("mma.sync.aligned.m16n8k16.row.col.f32.bf16.bf16.f32 {%0,%1,%2,%3},{%4,%5,%6,%7},{%8,%9},{%0,%1,%2,%3};"
               : "+f"(c[0]), "+f"(c[1]), "+f"(c[2]), "+f"(c[3]) : "r"(a0), "r"(a1), "r"(a2), "r"(a3), "r"(b0), "r"(b1));
}
__device__ __forceinline__ void mma16816z(float (&c)[4], uint32_t a0, uint32_t a1, uint32_t a2, uint32_t a3, uint32_t b0, uint32_t b1) {
  asm volatile("mma.sync.aligned.m16n8k16.row.col.f32.bf16.bf16.f32 {%0,%1,%2,%3},{%4,%5,%6,%7},{%8,%9},{%10,%10,%10,%10};"
               : "=f"(c[0]), "=f"(c[1]), "=f"(c[2]), "=f"(c[3]) : "r"(a0), "r"(a1), "r"(a2), "r"(a3), "r"(b0), "r"(b1), "f"(0.f));
}
__device__ __forceinline__ void mma1688(float (&c)[4], uint32_t a0, uint32_t a1, uint32_t b0) {
  asm volatile("mma.sync.aligned.m16n8k8.row.col.f32.bf16.bf16.f32 {%0,%1,%2,%3},{%4,%5},{%6},{%0,%1,%2,%3};"
               : "+f"(c[0]), "+f"(c[1]), "+f"(c[2]), "+f"(c[3]) : "r"(a0), "r"(a1), "r"(b0));
}
__device__ __forceinline__ float quad_max(float v) { v = fmaxf(v, __shfl_xor_sync(~0u, v, 1)); return fmaxf(v, __shfl_xor_sync(~0u, v, 2)); }
__device__ __forceinline__ float quad_sum(float v) { v += __shfl_xor_sync(~0u, v, 1); return v + __shfl_xor_sync(~0u, v, 2); }
__device__ __forceinline__ uint32_t opaque(uint32_t v) { asm volatile("" : "+r"(v)); return v; }
__device__ __forceinline__ uint32_t tid_now() { uint32_t v; asm volatile("mov.u32 %0, %%tid.x;" : "=r"(v)); return v; }
__device__ __forceinline__ void arrive_after(uint32_t bar, float v) {
  asm volatile("{\n.reg .pred p, q;\n.reg .b32 c;\nmov.b32 c, %1;\nelect.sync _|q, 0xffffffff;\n"
               "L: @q mbarrier.arrive.shared::cta.b64 _, [%0];\nsetp.eq.u32 p, c, 0x7fedcba9;\nadd.u32 c, c, 1;\nsetp.ne.u32 q, c, c;\n@p bra L;\n}"
               ::"r"(bar), "r"(__float_as_uint(v)) : "memory");
}
__device__ __forceinline__ int since(int t0) { return (int)((uint32_t)clock() - (uint32_t)t0); }
__device__ __forceinline__ void until(int t0, uint32_t t) { while ((uint32_t)since(t0) < t) {} }
__device__ __forceinline__ void in_order() { const int t = (int)clock(); while (since(t) < 0) {} }
__device__ __forceinline__ void spin(int clocks) { until((int)clock(), clocks); }

constexpr float ATT_SCALE_LOG2E = 0.17677669529663687f * 1.4426950408889634f;

constexpr int T_XA = 2600;
constexpr int P_XB = 100;
constexpr int P_ACT = 140;
constexpr int T_Q2 = 3750;
constexpr int T_Q3 = 4150;
constexpr int T_XB = 8050;
constexpr int DELAY_ST = 150;
constexpr int T_W0 = 3200;
constexpr int T_G0 = 4500;
constexpr int T_G1 = 7250;
constexpr int P_G2 = 690;
constexpr int P_G2B = 820;
constexpr int F_G2A = 700;
constexpr int F_G2B = 750;
constexpr int P_Q = 240;
constexpr int T_W = 5500;
constexpr int P_W = 1200;
constexpr int DELAY_HELP = 3000;

struct Pipe {
  const uint2* tab;
  uint32_t bars, peer_bars;
  uint2 nx;
  uint32_t prev;
  bool ready;
  bool lead;
  __device__ __forceinline__ uint2 begin(int n) {
    const uint2 e = nx;
    nx = tab[n + 1];
    if (!ready) {
      mbar_wait(bars + (e.y & 0x3ff), (e.y >> 10) & 1);
      mbar_wait(bars + ((e.y >> 16) & 0x7ff), e.y >> 31);
    }
    ready = false;
    return e;
  }
  __device__ __forceinline__ void release_now(uint32_t y) {
    asm volatile("{\n.reg .pred p, q;\n.reg .b32 c;\nmov.b32 c, %2;\nelect.sync _|q, 0xffffffff;\nsetp.ne.and.u32 q, c, 0, q;\n"
                 "L: @q mbarrier.arrive.shared::cta.b64 _, [%0];\n@q mbarrier.arrive.shared::cluster.b64 _, [%1];\n"
                 "setp.eq.u32 p, c, 1;\nadd.u32 c, c, 1;\n@p bra L;\n}"
                 ::"r"(bars + 512 + (y & 0x3ff)), "r"(peer_bars + 512 + (y & 0x3ff)), "r"(opaque(lead ? y & 0x800 : 0)) : "memory");
  }
  template <bool PAUSES = false> __device__ __forceinline__ void end(uint32_t y) {
    const bool r0 = mbar_test(bars + (nx.y & 0x3ff), (nx.y >> 10) & 1), r1 = mbar_test(bars + ((nx.y >> 16) & 0x7ff), nx.y >> 31);
    wg_wait<1>();
    release(prev);
    prev = y;
    if (PAUSES && (y & 0x1000)) { wg_wait<0>(); release(y); prev = 0; }
    ready = __all_sync(~0u, r0 && r1);
  }
  __device__ __forceinline__ void release(uint32_t y) {
    if (lead && (y & 0x800)) { if (elect_one()) { mbar_arrive(bars + 512 + (y & 0x3ff)); mbar_arrive_remote(peer_bars + 512 + (y & 0x3ff)); } }
  }
};
__device__ __forceinline__ constexpr uint32_t qa(int q) { return (q >> 1) * 256 + (q & 1) * 2; }

__device__ __forceinline__ uint32_t img_pos(uint32_t w, uint32_t lane) { return (w * 16 + (lane >> 2)) * 4 + ((lane & 3) ^ (lane >> 3)); }
__device__ __forceinline__ uint32_t img_line(uint32_t w, uint32_t lane) { return (lane >> 3) * 256 + w * 64 + (lane & 7) * 8; }

template <int MULTICAST>
__device__ __forceinline__ void tiles(uint32_t bars, const uint2* tab, uint2& nx, int n0, int n1, uint32_t dst, const char* src, uint32_t bytes,
                                      const uint32_t* cnt, uint32_t target, int pace, int head) {
  int due = 0;
#pragma unroll 1
  for (int n = n0; n < n1; n++) {
    const uint2 e = nx;
    nx = tab[n + 1];
    const uint32_t fb = bars + (e.y & 0x3ff);
    mbar_expect_tx(fb, (e.y >> 29) << 13);
    if (e.x & 0x1000000) {
      while ((int32_t)(ld_relaxed_line(cnt + ((e.x >> 25) & 31)) - target) < 0) {}
      asm volatile("fence.acquire.gpu;" ::: "memory"); fence_async_glob();
      if (!MULTICAST) due = since(head);
    }
    mbar_wait(bars + (e.x & 0x7ff), e.x >> 31);
    if (MULTICAST) bulk_g2s_mc(dst + (e.y & 0x3c000), src + (e.x & 0x3fc000), bytes, fb);
    else {
      until(due, (n - n0) * pace);
      bulk_g2s(dst + (e.y & 0x3c000), src + (e.x & 0x3fc000), bytes, fb);
    }
  }
}

template <int BOXES>
__device__ __forceinline__ void weights(uint32_t sb, uint2& nx, int& n, const CUtensorMap* m0, const CUtensorMap* m1, const CUtensorMap* m2, int c0, int c1, int c2, int dk) {
  const uint32_t bars = sb + BAR_OFF;
#pragma unroll 1
  for (bool more = true; more; n++) {
    const uint2 e = nx;
    nx = c_w[0][n + 1];
    more = !(e.y & 0x20000);
    const uint32_t fb = bars + (e.y & 0x3ff), dst = sb + W_OFF + (e.y & 0x1e000);
    const int k0 = (e.y >> 24) + dk;
    if (e.x & 0x7ff) mbar_wait(bars + (e.x & 0x7ff), (e.x >> 15) & 1);
    mbar_wait(bars + ((e.x >> 16) & 0x7ff), e.x >> 31);
    if (BOXES == 2) { tma5d_once(dst, m0, fb, c0, k0); tma5d_once(dst + 8192, m1, fb, c1, k0); }
    else { tma5d(dst, m0, fb, c0, k0); tma5d(dst + 8192, m1, fb, c1, k0); tma5d(dst + 16384, m2, fb, c2, k0); }
  }
}

__device__ __forceinline__ void mod_slice(uint32_t sb, uint32_t* dst, uint32_t tag, uint32_t w, uint32_t lane) {
  float e[4];
#pragma unroll 1
  for (int kb = 0; kb < 4; kb++) {
    mbar_wait(sb + BAR_OFF + B_SL + 8 * kb, 0);
    wg_fence();
#pragma unroll
    for (int q = 0; q < 4; q++) wgmma_n8(e, make_desc(SMEM_BASE + SL_OFF + kb * 8192, 8192) + q * 128, make_desc(SMEM_BASE + TAB_OFF + 4096 + kb * 256, 16) + q * 2, kb | q);
    wg_commit();
  }
  wg_wait<0>();
  fence_regs(e);
  if ((lane & 3) == 0) { st_relaxed(dst + w * 16 + (lane >> 2), tagf(e[0], tag)); st_relaxed(dst + w * 16 + 8 + (lane >> 2), tagf(e[2], tag)); }
  if (w == 0 && lane == 0) mbar_arrive(sb + BAR_OFF + B_SLE);
  __syncwarp();
}

__device__ __forceinline__ int mod_group(int job, int hc) { return (job >> 1) * 16 + hc * 4 + (job & 1) * 2; }

template <bool BY_SM>
__global__ void __cluster_dims__(2, 1, 1) __launch_bounds__(NTHREADS, 1) fused_kernel(const Ptrs Q, const __grid_constant__ Params P) {
  extern __shared__ __align__(1024) uint8_t smem_raw[];
  const int t0 = (int)clock();
  int cta = blockIdx.x;
  {
    uint32_t smid;
    asm volatile("mov.u32 %0, %%smid;" : "=r"(smid));
    const int tp = smid >> 1;
    const int cl = tp < 32 ? tp : (tp < 60 ? tp + 1 + (tp - 32) / 7 : (tp < 62 ? tp + 4 : (tp - 58) * 8));
    if (BY_SM) cta = cl * 2 + (cta & 1);
    cta = __shfl_sync(~0u, cta, 0);
  }
  const int grp = cta >> 4, j = cta & 15, rank = cta & 1, typ = j >> 3;
  const int wg = __shfl_sync(~0u, (int)threadIdx.x >> 7, 0);
  const int warp = __shfl_sync(~0u, (int)threadIdx.x >> 5, 0);
  const uint32_t sb = mapa(SMEM_BASE, rank), bars = sb + BAR_OFF;
  if (warp == 10 && cta < NCTA && elect_one()) {
    prefetch_tmap(&P.mWm2);
#pragma unroll
    for (int i = 0; i < 4; i++) mbar_init(bars + B_SL + 8 * i, 1);
    fence_async_smem();
    if (cta < 64) {
#pragma unroll
      for (int i = 0; i < 4; i++) {
        mbar_expect_tx(bars + B_SL + 8 * i, 8192);
        tma2d_once(sb + SL_OFF + i * 8192, &P.mWm2, bars + B_SL + 8 * i, ((cta >> 4) & 1) * D_ + (cta >> 5) * 256 + ((cta >> 2) & 3) * 64, (cta & 3) * 256 + i * 64);
      }
    }
  }
  __syncwarp();

  if (cta >= NCTA) {
    const uint32_t lane = tid_now() & 31, cf = sb + 196608, hb = cf + 16384;
    const int hc = cta - NCTA;
    if (threadIdx.x == 0) {
#pragma unroll 1
      for (int i = 0; i < 48; i++) mbar_init(hb + 8 * i, 1);
#pragma unroll 1
      for (int i = 0; i < 24; i++) mbar_init(bars + 8 * i, (i >> 1) == 6 ? 4 : 1);
    }
    const uint32_t ep = ld_relaxed(&Q.s->ep[cta * 32 + lane]) + 1;
#pragma unroll 1
    for (int kb = warp; kb < 16; kb += 12) {
      const uint32_t cv = ((const uint32_t*)Q.c)[kb * 32 + lane];
      sts32(cf + kb * 256 + (lane & 3) * 4 + (((lane >> 2) ^ ((2 * kb) & 7)) << 4), pack_bf16(silu_f(bf_lo(cv)), silu_f(bf_hi(cv))));
    }
    fence_async_smem();
    __syncthreads();
    if (wg == 2) {
      if (elect_one()) {
        spin(DELAY_HELP);
        uint32_t s = warp & 3, ph = 1;
#pragma unroll 1
        for (int n = (warp >> 1) & 1; n < 8 * 16; n += 2) {
          mbar_wait(hb + 8 * (24 + s), ph);
          mbar_expect_tx(hb + 8 * s, 8192);
          tma2d_once(sb + s * 8192, &P.mWm2, hb + 8 * s, (32 + mod_group(n >> 4, hc) + (warp & 1)) * 64, (n & 15) * 64);
          s += 4; if (s >= 24) { s -= 24; ph ^= 1; }
        }
      }
      __syncwarp();
      if (warp == 8) Q.s->ep[cta * 32 + lane] = ep;
    } else {
      uint32_t s = wg, ph = 0;
#pragma unroll 1
      for (int job = 0; job < 8; job++) {
        float e[4];
#pragma unroll 1
        for (int kb = 0; kb < 16; kb += 4) {
#pragma unroll 1
          for (int i = 0; i < 4; i++) {
            mbar_wait(hb + 8 * (s + 2 * i), ph);
            wg_fence();
#pragma unroll
            for (int q = 0; q < 4; q++)
              wgmma_n8(e, make_desc(SMEM_BASE, 8192) + (s + 2 * i) * 512 + q * 128, make_desc(SMEM_BASE + 196608, 16) + (kb + i) * 16 + q * 2, kb | i | q);
            wg_commit();
          }
          wg_wait<0>();
          if ((warp & 3) == 0 && elect_one()) {
#pragma unroll
            for (int i = 0; i < 4; i++) mbar_arrive(hb + 8 * (24 + s + 2 * i));
          }
          s += 8; if (s >= 24) { s -= 24; ph ^= 1; }
        }
        fence_regs(e);
        if ((lane & 3) == 0) {
          uint32_t* dst = Q.s->modp + (mod_group(job, hc) + wg) * 64 + (warp & 3) * 16 + (lane >> 2);
          st_relaxed(dst, tagf(e[0], tag_of(ep))); st_relaxed(dst + 8, tagf(e[2], tag_of(ep)));
          const uint32_t g = pack_bf16(2.f * __uint_as_float(tagf(e[0], tag_of(ep))), 2.f * __uint_as_float(tagf(e[2], tag_of(ep))));
          const uint32_t a = sb + PAR_OFF + ((job & 1) * 4 + wg * 2 + ((warp >> 1) & 1)) * 64 + (lane >> 3) * 16 + (warp & 1) * 8 + ((lane >> 2) & 1) * 2;
          asm volatile("st.shared.u16 [%0], %1;\nst.shared.u16 [%0 + 4], %2;" ::"r"(a), "h"((uint16_t)g), "h"((uint16_t)(g >> 16)) : "memory");
        }
        __syncwarp();
      }
    }
    __syncthreads();
    if (warp == 8) {
      if (only_one()) {
        mbar_expect_tx(bars + 64, N_HK * 32768);
#pragma unroll 1
        for (int i = 0; i < 4 * N_HK; i++) tma5d(sb + i * 8192, &P.mWd, bars + 64, hc * 256 + (i & 3) * 64, (i >> 2) * 2);
        uint32_t n = 0;
#pragma unroll 1
        for (int rb = 0; rb < 16; rb++) {
          while ((int32_t)(ld_relaxed(Q.s->cnt + (rb & 7) * 32 + (rb < 8 ? G_HK : 8 + G_ACT)) - (rb < 8 ? 4 * N_HK : 64) * ep) < 0) __nanosleep(50);
          asm volatile("fence.acquire.gpu;" ::: "memory"); fence_async_glob();
#pragma unroll 1
          for (int i = 0; i < 2 * N_HK; i++, n++) {
            mbar_wait(bars + 128 + 8 * (n & 7), ((n >> 3) & 1) ^ 1);
            mbar_expect_tx(bars + 8 * (n & 7), 8192);
            bulk_g2s(sb + 98304 + (n & 7) * 8192, Q.s->img + (size_t)((rb & 7) * N_TILES + T_ACT + (rb >> 3) * 56 + i % N_HK) * 1024 + i / N_HK * 512, 8192, bars + 8 * (n & 7));
          }
        }
      }
    } else if (warp >= 10) {
      if (only_one()) {
        const int q = warp & 1;
#pragma unroll 1
        for (int rb = 0; rb < 16; rb++) {
          mbar_wait(bars + 96 + 8 * q, rb & 1);
#pragma unroll 1
          for (int i = 0; i < 8; i++)
            asm volatile("cp.reduce.async.bulk.global.shared::cta.bulk_group.add.noftz.bf16 [%0], [%1], 4096;"
                         ::"l"(Q.s->img + (size_t)((rb & 7) * N_TILES + T_X1 + (rb >> 3) * 16 + hc * 4 + (i >> 1)) * 1024 + q * 512 + (i & 1) * 256), "r"(sb + 163840 + q * 32768 + i * 4096) : "memory");
          bulk_commit();
          bulk_wait_read();
          mbar_arrive(bars + 80 + 8 * q);
        }
        asm volatile("cp.async.bulk.wait_group 0;" ::: "memory");
        fence_async_glob(); asm volatile("fence.acq_rel.gpu;" ::: "memory");
#pragma unroll 1
        for (int i = 0; i < 8; i++) red_relaxed(Q.s->cnt + i * 32 + G_X1, 8);
      }
    } else if (wg < 2) {
      const uint32_t w = warp & 3;
      uint32_t n = wg * N_HK;
      mbar_wait(bars + 64, 0);
#pragma unroll 1
      for (int rb = 0; rb < 16; rb++) {
        float acc[128];
        mbar_wait(bars + 112 + 8 * wg, (rb & 1) ^ wg ^ 1);
#pragma unroll 1
        for (int kb = 0; kb < N_HK; kb++, n++) {
          mbar_wait(bars + 8 * (n & 7), (n >> 3) & 1);
          const uint32_t da = make_desc(SMEM_BASE + 98304, 16) + (n & 7) * 512, db = make_desc(SMEM_BASE, 8192) + kb * 2048;
          wg_fence();
#pragma unroll
          for (int q = 0; q < 4; q++) wg_n256<H64, H128>(acc, da + qa(q), db + 128 * q, q ? 1 : kb);
          wg_commit();
          wg_wait<1>();
          if (kb && w == 0 && elect_one()) mbar_arrive(bars + 128 + 8 * ((n - 1) & 7));
        }
        if (w == 0 && elect_one()) mbar_arrive(bars + 120 - 8 * wg);
        wg_wait<0>();
        if (w == 0 && elect_one()) mbar_arrive(bars + 128 + 8 * ((n - 1) & 7));
        mbar_wait(bars + 80 + 8 * wg, (rb & 1) ^ 1);
        fence_regs(acc);
        const uint32_t ln = tid_now() & 31, st = sb + 163840 + wg * 32768 + img_pos(w, ln) * 16;
        uint4 gn = lds128(sb + PAR_OFF + (ln & 3) * 16);
#pragma unroll
        for (int c = 0; c < 8; c++) {
          const uint4 g = gn;
          if (c < 7) gn = lds128(sb + PAR_OFF + (c + 1) * 64 + (ln & 3) * 16);
#pragma unroll
          for (int f = 0; f < 2; f++) {
            const float* a = &acc[16 * c + 2 * f];
            sts128(st + c * 4096 + f * 512, hmul2_bf16(g.x, pack_bf16(a[0], a[1])), hmul2_bf16(g.y, pack_bf16(a[4], a[5])),
                   hmul2_bf16(g.z, pack_bf16(a[8], a[9])), hmul2_bf16(g.w, pack_bf16(a[12], a[13])));
          }
        }
        n += N_HK;
        fence_async_smem(); __syncwarp();
        if (elect_one()) mbar_arrive(bars + 96 + 8 * wg);
      }
    }
  } else if (wg < 2) {
    asm volatile("setmaxnreg.inc.sync.aligned.u32 232;");
    const int w = warp & 3, rb = wg * 8 + grp;
    uint4* const img = Q.s->img + (size_t)grp * (N_TILES * 1024);
    uint32_t* const cnt = Q.s->cnt + grp * 32 + wg * 8;
    {
      const uint32_t tid = tid_now() & 127, lane = tid & 31;
      const uint32_t row = 8 * j + 2 * w + (lane >> 4);
      if (tid < 64) st_relaxed_b64(Q.s->stat + ((rb * 2 + rank) * 8 + (j >> 1)) * 64 + tid, 0, 0);
      uint4* dst = img + (T_H + wg * 16 + ((lane >> 3) & 1)) * 1024 + row * 8 + ((lane ^ row) & 7);
      const uint4* back = img + (T_H + wg * 16 + (lane >> 1)) * 1024 + (8 * j + 2 * w + (lane & 1)) * 8;
      const uint32_t tab = sb + TAB_OFF + (lane & 15) * 16;
      if (wg) {
        const uint32_t ep0 = ld_relaxed(&Q.s->ep[cta * 32 + lane]);
        uint32_t* mdst = Q.s->mod0 + ((cta >> 5) * 4 + (cta & 3)) * 512 + ((cta >> 2) & 7) * 64;
        const uint32_t cv = ldg32(Q.c + (cta & 3) * 256 + tid * 2);
        if (tid < 64) st_relaxed(mdst + tid, 0);
        uint4* mbox = Q.s->halo + (size_t)(grp * 16 + j) * 128 + tid;
        st_relaxed_v4(mbox, ~0u, ~0u, ~0u, ~0u); st_relaxed_v4(mbox + 128 * 128, ~0u, ~0u, ~0u, ~0u);
        const uint32_t s0 = ld_relaxed(mbox), s1 = ld_relaxed(mbox + 128 * 128);
        named_sync(0, NTHREADS);
        asm volatile("barrier.cluster.arrive.relaxed.aligned;" ::: "memory");
        in_order();
        sts32(sb + TAB_OFF + 4096 + w * 256 + (lane & 3) * 4 + (((lane >> 2) ^ (2 * w)) << 4), pack_bf16(silu_f(bf_lo(opaque(cv))), silu_f(bf_hi(cv))));
        fence_async_smem();
        if (__any_sync(~0u, (opaque(s0) & opaque(s1)) == 0)) __nanosleep(1);
        named_sync(2, 128);
        asm volatile("barrier.cluster.wait.aligned;" ::: "memory");
        const uint32_t ep = tag_of(opaque(ep0) + 1);
        uint4 xa[4];
#pragma unroll
        for (int i = 0; i < 4; i++) xa[i] = make_uint4(0, 0, 0, 0);
#pragma unroll 1
        for (int s = 0; s < 2; s++) {
          if ((cta >> 6) == s) mod_slice(sb, mdst, ep, w, lane);
          until(t0, s ? T_G1 : T_G0);
          const uint4* ms = (const uint4*)Q.s->mod0 + (2 * s + rank) * 512 + tid;
          uint4 p[4];
#pragma unroll
          for (int i = 0; i < 4; i++) p[i] = make_uint4(0, 0, 0, 0);
          uint32_t it = 0;
          do {
#pragma unroll
            for (int i = 0; i < 4; i++) if (tag_bad(p[i], ep)) p[i] = ld_relaxed_v4(ms + i * 128);
          } while (__any_sync(~0u, tag_bad(p[0], ep) | tag_bad(p[1], ep) | tag_bad(p[2], ep) | tag_bad(p[3], ep)) && ++it < POLL_MAX);
#define F4(f) ((__uint_as_float(p[0].f) + __uint_as_float(p[1].f)) + (__uint_as_float(p[2].f) + __uint_as_float(p[3].f)))
          uint32_t c0 = pack_bf16(F4(x), F4(y)), c1 = pack_bf16(F4(z), F4(w));
#undef F4
          if (w >= 2) { c0 = hadd2_bf16(c0, 0x3f803f80u); c1 = hadd2_bf16(c1, 0x3f803f80u); }
          const uint32_t ta = TAB_OFF + (tid >> 6) * 2048 + (2 * s + rank) * 512 + (tid & 63) * 8, peer = mapa(SMEM_BASE, rank ^ 1);
          asm volatile("st.async.weak.shared::cluster.mbarrier::complete_tx::bytes.v2.b32 [%0], {%2,%3}, [%1];" ::"r"(peer + ta), "r"(peer + BAR_OFF + B_ST + 8 * s), "r"(c0), "r"(c1) : "memory");
          sts64(sb + ta, c0, c1);
          if (s == 0) {
            mbar_wait(bars + B_XB, 0);
#pragma unroll
            for (int i = 0; i < 4; i++) xa[i] = lds128(sb + 4 * 16384 + (row & 7) * 2048 + 1024 + i * 256 + (lane & 15) * 16);
            landed(xa[0].x & xa[1].x & xa[2].x & xa[3].x);
          }
          __syncwarp();
          if (elect_one()) mbar_expect_tx(bars + B_ST + 8 * s, 256);
        }
        mbar_wait(bars + B_ST + 8, 0);
        const float m = __uint_as_float(lds32(sb + TAB_OFF + 6144 + tid * 8)), v = __uint_as_float(lds32(sb + TAB_OFF + 6148 + tid * 8));
#pragma unroll
        for (int i = 4; i < 8; i++) {
          const uint4 a = lds128(tab + i * 256), c = lds128(tab + 2048 + i * 256);
#define NRM(x) pack_bf16(fmaf(bf_lo(x), v, m), fmaf(bf_hi(x), v, m))
          stg128(dst - 16384 + i * 2048, hfma2_bf16(NRM(xa[i & 3].x), c.x, a.x), hfma2_bf16(NRM(xa[i & 3].y), c.y, a.y),
                 hfma2_bf16(NRM(xa[i & 3].z), c.z, a.z), hfma2_bf16(NRM(xa[i & 3].w), c.w, a.w));
#undef NRM
        }
        publish(lane >= 16 ? ld_relaxed(back - 16384) : 0, cnt - 8 + G_H1, 1);
      } else {
        named_sync(0, NTHREADS);
        asm volatile("barrier.cluster.arrive.relaxed.aligned;\nbarrier.cluster.wait.aligned;" ::: "memory");
      }
      mbar_wait(bars + B_XB + 8 * wg, 0);
      float d[64], m = 0.f, v = 0.f, m2 = 0.f, v2 = 0.f;
#pragma unroll
      for (int i = 0; i < 8; i++) {
        const uint4 t = lds128(sb + (4 + wg) * 16384 + (row & 7) * 2048 + i * 256 + (lane & 15) * 16);
        const uint32_t x[4] = {t.x, t.y, t.z, t.w};
#pragma unroll
        for (int e = 0; e < 4; e++) {
          const float d0 = bf_lo(x[e]), d1 = bf_hi(x[e]);
          d[8 * i + 2 * e] = d0; d[8 * i + 2 * e + 1] = d1;
          m += d0; m2 += d1; v = fmaf(d0, d0, v); v2 = fmaf(d1, d1, v2);
        }
      }
      m += m2; v += v2;
#pragma unroll
      for (int i = 1; i < 16; i *= 2) { m += __shfl_xor_sync(~0u, m, i); v += __shfl_xor_sync(~0u, v, i); }
      m *= 1.f / D_;
      v = rsqrtf(fmaxf(fmaf(-m, m, v * (1.f / D_)), 0.f) + 1e-5f);
      m = -m * v;
      if (!wg) {
        sts64(sb + TAB_OFF + 6144 + tid * 8, __float_as_uint(m), __float_as_uint(v));
        __syncwarp();
        if (elect_one()) mbar_arrive(bars + B_ST + 8);
      }
      mbar_wait(bars + B_ST, 0);
#pragma unroll
      for (int s = 0; s < 2; s++) {
        if (s > wg) break;
#pragma unroll
        for (int i = 4 * s; i < 4 * s + 4; i++) {
          const uint4 a = lds128(tab + i * 256), c = lds128(tab + 2048 + i * 256);
#define NRM(e) pack_bf16(fmaf(d[8 * i + 2 * e], v, m), fmaf(d[8 * i + 2 * e + 1], v, m))
          stg128(dst + i * 2048, hfma2_bf16(NRM(0), c.x, a.x), hfma2_bf16(NRM(1), c.y, a.y), hfma2_bf16(NRM(2), c.z, a.z), hfma2_bf16(NRM(3), c.w, a.w));
#undef NRM
        }
      }
      publish(wg || lane < 16 ? ld_relaxed(back) : 0, cnt + G_H0, 1);
    }

    Pipe pp;
    pp.tab = c_cons[wg];
    pp.bars = bars; pp.peer_bars = mapa(bars, rank ^ 1); pp.lead = w == 0; pp.prev = 0; pp.ready = false;
    pp.nx = pp.tab[0];
    const uint32_t dA0 = make_desc(SMEM_BASE, 16), dB0 = make_desc(SMEM_BASE + W_OFF, 8192);
    const uint32_t dAo = dA0 + rank * 512, dAp = dA0 + 512 - rank * 512;

    {
      float acc[2][96];
#pragma unroll 1
      for (int n = 0; n < 14; n++) {
        const uint2 e = pp.begin(n);
        const uint32_t da = dA0 + (e.x & 0xffff), db = dB0 + (e.x >> 16);
        wg_fence();
#pragma unroll
        for (int q = 0; q < 4; q++) {
          wg_n192<H128, H128>(acc[0], da + 2 * q, db + 128 * q, q ? 1 : n);
          wg_n192<H128, H128>(acc[1], da + 2 * q + 512, db + 128 * q, q ? 1 : n);
        }
        wg_commit();
        pp.template end<true>(e.y);
      }
      const uint2 e0 = pp.begin(14), e1 = pp.begin(15);
#pragma unroll
      for (int h = 1; h >= 0; h--) {
        wg_fence();
#pragma unroll
        for (int q = 0; q < 4; q++) wg_n192<H128, H128>(acc[h], dA0 + (e0.x & 0xffff) + 2 * q + 512 * h, dB0 + (e0.x >> 16) + 128 * q, 1);
#pragma unroll
        for (int q = 0; q < 4; q++) wg_n192<H128, H128>(acc[h], dA0 + (e1.x & 0xffff) + 2 * q + 512 * h, dB0 + (e1.x >> 16) + 128 * q, 1);
        wg_commit();
        if (h) { wg_wait<1>(); pp.release(pp.prev); }
      }
      if (pp.lead && elect_one()) mbar_arrive(bars + B_Q + 8 * wg);
      const uint2 ea = pp.begin(16);
      const uint32_t lane = tid_now() & 31, g = lane >> 2, t = lane & 3;
      const uint32_t hal = sb + (ea.x & 0xffff) * 16 + w * 2048 + lane * 16;
      uint4* mbox = Q.s->halo + (size_t)(rb * 16 + j) * 128 + lane;
      const bool first = w == 0 && grp == 0;
      uint32_t qp[2][8][2], kp[2][8][2], vp[2][8][2];
      uint4 hk[2][2], hw[2][2];
#pragma unroll
      for (int h = 1; h >= 0; h--) {
        if (h) wg_wait<1>(); else { in_order(); wg_wait<0>(); pp.release(e0.y); pp.release_now(e1.y); }
        fence_regs(acc[h]);
#pragma unroll
        for (int i = 0; i < 8; i++) {
          kp[h][i][1] = pack_bf16(acc[h][32 + 4 * i + 2], acc[h][32 + 4 * i + 3]);
          vp[h][i][1] = pack_bf16(acc[h][64 + 4 * i + 2], acc[h][64 + 4 * i + 3]);
        }
        if (h == 1 && w == 3 && grp < 7) {
#pragma unroll
          for (int d = 0; d < 2; d++) {
            st_relaxed_v4(mbox + 16 * 128 + d * 32, kp[h][4 * d][1], kp[h][4 * d + 1][1], kp[h][4 * d + 2][1], kp[h][4 * d + 3][1]);
            st_relaxed_v4(mbox + 16 * 128 + d * 32 + 64, vp[h][4 * d][1], vp[h][4 * d + 1][1], vp[h][4 * d + 2][1], vp[h][4 * d + 3][1]);
          }
        }
        if (h == 0) {
#pragma unroll
          for (int d = 0; d < 2; d++) {
            hk[0][d] = hw[0][d] = make_uint4(0, 0, 0, 0);
            if (w == 0) { hk[0][d] = ld_relaxed_v4(mbox + d * 32); hw[0][d] = ld_relaxed_v4(mbox + d * 32 + 64); }
          }
        }
#pragma unroll
        for (int i = 0; i < 8; i++) vp[h][i][1] = movm(vp[h][i][1]);
        if (h == 0 || w < 3) {
#pragma unroll
          for (int d = 0; d < 2; d++) {
            sts128(hal + 2048 + h * 8192 + d * 1024, kp[h][4 * d][1], kp[h][4 * d + 1][1], kp[h][4 * d + 2][1], kp[h][4 * d + 3][1]);
            sts128(hal + 2048 + h * 8192 + d * 1024 + 512, vp[h][4 * d][1], vp[h][4 * d + 1][1], vp[h][4 * d + 2][1], vp[h][4 * d + 3][1]);
          }
        }
        if (h == 0) {
          named_sync(1 + wg, 128);
#pragma unroll
          for (int d = 0; d < 2; d++) {
            if (w) { hk[0][d] = lds128(hal + d * 1024); hw[0][d] = lds128(hal + d * 1024 + 512); }
            hk[1][d] = lds128(hal + 8192 + d * 1024); hw[1][d] = lds128(hal + 8192 + d * 1024 + 512);
          }
        }
#pragma unroll
        for (int i = 0; i < 8; i++) {
          kp[h][i][0] = opaque(pack_bf16(acc[h][32 + 4 * i], acc[h][32 + 4 * i + 1]));
          vp[h][i][0] = movm(pack_bf16(acc[h][64 + 4 * i], acc[h][64 + 4 * i + 1]));
          qp[h][i][0] = opaque(pack_bf16(acc[h][4 * i], acc[h][4 * i + 1]));
          qp[h][i][1] = opaque(pack_bf16(acc[h][4 * i + 2], acc[h][4 * i + 3]));
        }
      }
      if (w == 0) {
        for (uint32_t it = 0; grp > 0 && it < POLL_MAX && __any_sync(~0u, empty(hk[0][0]) || empty(hk[0][1]) || empty(hw[0][0]) || empty(hw[0][1])); it++) {
#pragma unroll
          for (int d = 0; d < 2; d++) { hk[0][d] = ld_relaxed_v4(mbox + d * 32); hw[0][d] = ld_relaxed_v4(mbox + d * 32 + 64); }
        }
#pragma unroll
        for (int d = 0; d < 2; d++)
          hw[0][d] = first ? make_uint4(0, 0, 0, 0) : make_uint4(movm(hw[0][d].x), movm(hw[0][d].y), movm(hw[0][d].z), movm(hw[0][d].w));
      }
      const uint32_t hv[2][8] = {{hw[0][0].x, hw[0][0].y, hw[0][0].z, hw[0][0].w, hw[0][1].x, hw[0][1].y, hw[0][1].z, hw[0][1].w},
                                 {hw[1][0].x, hw[1][0].y, hw[1][0].z, hw[1][0].w, hw[1][1].x, hw[1][1].y, hw[1][1].z, hw[1][1].w}};
      landed(hw[0][0].x & hw[0][1].x & hw[1][0].x & hw[1][1].x);
      float s0[4][4], s1[4][4], s2[4][4];
#pragma unroll
      for (int c = 3; c >= 0; c--) {
        const int h = c >> 1, b = (c & 1) * 4;
        mma16816z(s1[c], qp[h][b][0], qp[h][b][1], qp[h][b + 1][0], qp[h][b + 1][1], kp[h][b][0], kp[h][b + 1][0]);
        mma16816z(s2[c], qp[h][b][0], qp[h][b][1], qp[h][b + 1][0], qp[h][b + 1][1], kp[h][b][1], kp[h][b + 1][1]);
        mma16816z(s0[c], qp[h][b][0], qp[h][b][1], qp[h][b + 1][0], qp[h][b + 1][1], hk[h][c & 1].x, hk[h][c & 1].y);
      }
#pragma unroll
      for (int c = 3; c >= 0; c--) {
        const int h = c >> 1, b = (c & 1) * 4 + 2;
        mma16816(s1[c], qp[h][b][0], qp[h][b][1], qp[h][b + 1][0], qp[h][b + 1][1], kp[h][b][0], kp[h][b + 1][0]);
        mma16816(s2[c], qp[h][b][0], qp[h][b][1], qp[h][b + 1][0], qp[h][b + 1][1], kp[h][b][1], kp[h][b + 1][1]);
        mma16816(s0[c], qp[h][b][0], qp[h][b][1], qp[h][b + 1][0], qp[h][b + 1][1], hk[h][c & 1].z, hk[h][c & 1].w);
      }
      arrive_after(bars + B_R + 16 * wg, s0[0][0]);
      const bool c0 = 2 * t <= g, c1 = 2 * t + 1 <= g;
      const uint32_t mcur = (c0 ? 0x0000ffffu : 0u) | (c1 ? 0xffff0000u : 0u);
      uint32_t pa[4], pb[4];
#pragma unroll
      for (int c = 3; c >= 0; c--) {
        if (c < 2 && first) { s0[c][0] = -INFINITY; s0[c][1] = -INFINITY; }
        float a0 = c0 ? s1[c][0] : s0[c][0], a1 = c1 ? s1[c][1] : s0[c][1];
        float b0 = c0 ? s2[c][2] : s1[c][2], b1 = c1 ? s2[c][3] : s1[c][3];
        const float ma = quad_max(fmaxf(a0, a1)), mb = quad_max(fmaxf(b0, b1));
        a0 = ex2((a0 - ma) * ATT_SCALE_LOG2E); a1 = ex2((a1 - ma) * ATT_SCALE_LOG2E);
        b0 = ex2((b0 - mb) * ATT_SCALE_LOG2E); b1 = ex2((b1 - mb) * ATT_SCALE_LOG2E);
        const float ia = rcp(quad_sum(a0 + a1)), ib = rcp(quad_sum(b0 + b1));
        pa[c] = opaque(pack_bf16(a0 * ia, a1 * ia)); pb[c] = opaque(pack_bf16(b0 * ib, b1 * ib));
      }
      if (pp.lead) { mbar_wait(bars + B_R + 16 * wg, 0); pp.release(ea.y); }
      float o[16][4];
#pragma unroll
      for (int i = 0; i < 16; i++) mma16816z(o[i], pa[i >> 2] & mcur, pb[i >> 2] & ~mcur, 0u, pb[i >> 2] & mcur, vp[i >> 3][i & 7][0], vp[i >> 3][i & 7][1]);
#pragma unroll
      for (int i = 0; i < 16; i++) mma1688(o[i], pa[i >> 2] & ~mcur, 0u, hv[i >> 3][i & 7]);
      arrive_after(bars + B_R + 16 * wg + 8, o[15][0]);
      uint4* tile = img + (T_O + wg * 16 + j) * 1024;
      uint4* dst = tile + img_pos(w, lane);
#pragma unroll
      for (int c = 0; c < 4; c++)
#pragma unroll
        for (int f = 0; f < 2; f++) {
          stg128(dst + c * 256 + f * 32, pack_bf16(o[4 * c][2 * f], o[4 * c][2 * f + 1]), pack_bf16(o[4 * c + 1][2 * f], o[4 * c + 1][2 * f + 1]),
                 pack_bf16(o[4 * c + 2][2 * f], o[4 * c + 2][2 * f + 1]), pack_bf16(o[4 * c + 3][2 * f], o[4 * c + 3][2 * f + 1]));
        }
      publish(ld_relaxed(tile + img_line(w, lane)), cnt + G_O, 1);
    }

    {
      float acc[2][64];
      uint32_t xr[32];
      {
        const uint32_t lane = tid_now() & 31;
        const uint2 e = pp.begin(17);
        const uint32_t a0 = sb + (e.x & 0xffff) * 16 + (w * 16 + (lane & 15)) * 128 + (((lane >> 4) ^ (lane & 7)) << 4);
#pragma unroll
        for (int i = 0; i < 8; i++) ldsm4((a0 ^ ((i & 3) << 5)) + (i >> 2) * 8192, xr[4 * i], xr[4 * i + 1], xr[4 * i + 2], xr[4 * i + 3]);
        landed(xr[0] & xr[4] & xr[8] & xr[12] & xr[16] & xr[20] & xr[24] & xr[28]);
        named_sync(1 + wg, 128);
        pp.release(e.y);
      }
      pp.prev = 0;
#pragma unroll 1
      for (int n = 18; n < 24; n++) {
        const uint2 e = pp.begin(n);
        const uint32_t da = e.x & 0xffff, db = dB0 + (e.x >> 16);
        wg_fence();
#pragma unroll
        for (int q = 0; q < 4; q++) {
          wg_n128<H64, H128>(acc[0], dAo + da + qa(q), db + 128 * q, q ? 1 : n - 18);
          wg_n128<H64, H128>(acc[1], dAp + da + qa(q), db + 128 * q, q ? 1 : n - 18);
        }
        wg_commit();
        pp.template end<true>(e.y);
      }
      const uint2 e0 = pp.begin(24);
      const uint2 e1 = pp.begin(25);
#pragma unroll
      for (int h = 1; h >= 0; h--) {
        wg_fence();
#pragma unroll
        for (int q = 0; q < 4; q++) wg_n128<H64, H128>(acc[h], (h ? dAp : dAo) + (e0.x & 0xffff) + qa(q), dB0 + (e0.x >> 16) + 128 * q, 1);
#pragma unroll
        for (int q = 0; q < 4; q++) wg_n128<H64, H128>(acc[h], (h ? dAp : dAo) + (e1.x & 0xffff) + qa(q), dB0 + (e1.x >> 16) + 128 * q, 1);
        wg_commit();
      }
      const uint32_t tid = tid_now() & 127, lane = tid & 31;
      const uint2 ea = pp.begin(26);
      const uint32_t px = (ea.x & 0xffff) * 16 + tid * 16;
      wg_wait<1>();
      pp.release_now(pp.prev);
      fence_regs(acc[1]);
#pragma unroll
      for (int i = 0; i < 8; i++)
        st_async(pp.peer_bars - BAR_OFF + px + i * 2048, pp.peer_bars + (pp.nx.y & 0x3ff), pack_bf16(acc[1][8 * i], acc[1][8 * i + 1]), pack_bf16(acc[1][8 * i + 2], acc[1][8 * i + 3]),
                 pack_bf16(acc[1][8 * i + 4], acc[1][8 * i + 5]), pack_bf16(acc[1][8 * i + 6], acc[1][8 * i + 7]));
      wg_wait<0>();
      pp.release(e0.y); pp.release(e1.y); pp.release_now(ea.y);
      fence_regs(acc[0]);
      const uint32_t ep = tag_of(lds32(bars + ROLE_OFF + 4));
      mbar_wait(bars + B_PAR, 0);
      uint32_t pr[3][16];
#pragma unroll
      for (int i = 0; i < 4; i++) {
        const uint4 x = lds128(sb + PAR_OFF + (i >> 2) * 256 + (lane & 3) * 64 + (i & 3) * 16);
        pr[i >> 2][(i & 3) * 4] = x.x; pr[i >> 2][(i & 3) * 4 + 1] = x.y; pr[i >> 2][(i & 3) * 4 + 2] = x.z; pr[i >> 2][(i & 3) * 4 + 3] = x.w;
      }
      const uint2 eb = pp.begin(27);
      float sm[2] = {0.f, 0.f}, sq[2] = {0.f, 0.f};
#pragma unroll
      for (int c = 0; c < 8; c++) {
        const uint4 z = lds128(sb + px + c * 2048);
        const uint32_t zz[4] = {z.x, z.y, z.z, z.w};
#pragma unroll
        for (int b = 0; b < 4; b++) {
          const int i = 4 * c + b;
          xr[i] = hfma2_bf16(pr[0][i >> 1], hadd2_bf16(pack_bf16(acc[0][2 * i], acc[0][2 * i + 1]), zz[b]), xr[i]);
          const float d0 = bf_lo(xr[i]), d1 = bf_hi(xr[i]);
          acc[0][2 * i] = d0; acc[0][2 * i + 1] = d1;
          sm[i & 1] += d0 + d1;
          sq[i & 1] = fmaf(d0, d0, fmaf(d1, d1, sq[i & 1]));
        }
      }
      {
        const bool b0 = lane & 1;
        sm[0] = (b0 ? sm[1] : sm[0]) + __shfl_xor_sync(~0u, b0 ? sm[0] : sm[1], 1);
        sq[0] = (b0 ? sq[1] : sq[0]) + __shfl_xor_sync(~0u, b0 ? sq[0] : sq[1], 1);
        sm[0] += __shfl_xor_sync(~0u, sm[0], 2);
        sq[0] += __shfl_xor_sync(~0u, sq[0], 2);
      }
      uint2* ss = Q.s->stat + (rb * 2 + rank) * 512 + w * 16 + (lane >> 2) * 2 + (lane & 1);
      if (!(lane & 2)) st_relaxed_b64(ss + (j >> 1) * 64, tagf(sm[0], ep), tagf(sq[0], ep));
      named_sync(1 + wg, 128);
      pp.release(eb.y);
      mbar_wait(bars + B_PAR + 8, 0);
#pragma unroll
      for (int i = 4; i < 12; i++) {
        const uint4 x = lds128(sb + PAR_OFF + (i >> 2) * 256 + (lane & 3) * 64 + (i & 3) * 16);
        pr[i >> 2][(i & 3) * 4] = x.x; pr[i >> 2][(i & 3) * 4 + 1] = x.y; pr[i >> 2][(i & 3) * 4 + 2] = x.z; pr[i >> 2][(i & 3) * 4 + 3] = x.w;
      }
      {
        ss += (lane & 2) * 128;
        uint2 p[4];
#pragma unroll
        for (int i = 0; i < 4; i++) p[i] = make_uint2(0, 0);
        spin(DELAY_ST);
        uint32_t it = 0, bad;
        do {
          bad = 0;
#pragma unroll
          for (int i = 0; i < 4; i++) if (((p[i].x ^ ep) | (p[i].y ^ ep)) & 3u) p[i] = ld_relaxed_b64(ss + i * 64);
#pragma unroll
          for (int i = 0; i < 4; i++) bad |= (p[i].x ^ ep) | (p[i].y ^ ep);
        } while (__any_sync(~0u, bad & 3u) && ++it < POLL_MAX);
        float m = (__uint_as_float(p[0].x) + __uint_as_float(p[1].x)) + (__uint_as_float(p[2].x) + __uint_as_float(p[3].x));
        float v = (__uint_as_float(p[0].y) + __uint_as_float(p[1].y)) + (__uint_as_float(p[2].y) + __uint_as_float(p[3].y));
        m += __shfl_xor_sync(~0u, m, 2); v += __shfl_xor_sync(~0u, v, 2);
        m *= 1.f / D_;
        v = rsqrtf(fmaxf(fmaf(-m, m, v * (1.f / D_)), 0.f) + 1e-5f);
        m = -m * v;
#pragma unroll
        for (int r = 0; r < 2; r++) { sm[r] = __shfl_sync(~0u, m, r, 2); sq[r] = __shfl_sync(~0u, v, r, 2); }
      }
      uint4* tile = img + (T_H + wg * 16 + (j & 14)) * 1024 + rank * 512;
      uint4* dst = tile + img_pos(w, lane);
#pragma unroll
      for (int c = 0; c < 4; c++)
#pragma unroll
        for (int f = 0; f < 2; f++) {
          uint32_t y[4];
#pragma unroll
          for (int b = 0; b < 4; b++) {
            const int i = c * 4 + b;
            y[b] = hfma2_bf16(pack_bf16(fmaf(acc[0][4 * i + 2 * f], sq[f], sm[f]), fmaf(acc[0][4 * i + 2 * f + 1], sq[f], sm[f])), pr[2][i], pr[1][i]);
          }
          stg128(dst + (c >> 1) * 1024 + (c & 1) * 256 + f * 32, y[0], y[1], y[2], y[3]);
        }
      publish(ld_relaxed(tile + img_line(w, lane) + (lane >> 4) * 512), cnt + G_H2, 1);
#pragma unroll
      for (int c = 0; c < 4; c++)
#pragma unroll
        for (int f = 0; f < 2; f++) {
          stg128(dst + (T_X1 - T_H + (c >> 1)) * 1024 + (c & 1) * 256 + f * 32, xr[8 * c + f], xr[8 * c + 2 + f], xr[8 * c + 4 + f], xr[8 * c + 6 + f]);
        }
    }

    float acc[2][64], ax[32];
    uint32_t px_y;
    {
      float a3[2][96];
      pp.prev = 0;
#pragma unroll 1
      for (int n = 28; n < 44; n++) {
        const uint2 e = pp.begin(n);
        const uint32_t da = e.x & 0xffff, db = dB0 + (e.x >> 16);
        wg_fence();
#pragma unroll
        for (int q = 0; q < 4; q++) {
          wg_n192<H64, H128>(a3[0], dAo + da + qa(q), db + 128 * q, q ? 1 : n - 28);
          wg_n192<H64, H128>(a3[1], dAp + da + qa(q), db + 128 * q, q ? 1 : n - 28);
        }
        wg_commit();
        pp.end(e.y);
      }
      px_y = pp.nx.y;
      pp.nx = pp.tab[45]; pp.ready = false;
      mbar_wait(bars + ((px_y >> 16) & 0x7ff), px_y >> 31);
      wg_wait<0>();
      pp.release_now(pp.prev);
      fence_regs(a3[0]); fence_regs(a3[1]);
      pp.prev = 0;
#pragma unroll
      for (int i = 0; i < 4; i++)
        st_async(pp.peer_bars - 8192 + (tid_now() & 127) * 16 + i * 2048, pp.peer_bars + (px_y & 0x3ff), pack_bf16(a3[1][64 + 8 * i], a3[1][65 + 8 * i]),
                 pack_bf16(a3[1][66 + 8 * i], a3[1][67 + 8 * i]), pack_bf16(a3[1][68 + 8 * i], a3[1][69 + 8 * i]), pack_bf16(a3[1][70 + 8 * i], a3[1][71 + 8 * i]));
#pragma unroll
      for (int i = 0; i < 64; i++) { acc[0][i] = a3[0][i]; acc[1][i] = a3[1][i]; }
#pragma unroll
      for (int i = 0; i < 32; i++) ax[i] = a3[0][64 + i];
    }
    uint32_t seen, seen2;
#pragma unroll 1
    for (int T = 0;; T++) {
      wg_wait<0>();
      pp.release_now(pp.prev);
      fence_regs(acc[0]); fence_regs(acc[1]);
      pp.prev = 0;
      {
        const uint32_t lane = tid_now() & 31;
        uint4* tile = img + (T_ACT + wg * 56 + (T ? 8 + 16 * T : 0) + j) * 1024;
        uint4* tx = img + (T_ACT + wg * 56 + 16 + (j >> 1)) * 1024 + rank * 512;
        const int ts = (int)clock();
#pragma unroll
        for (int c = 0; c < 4; c++)
#pragma unroll
          for (int f = 0; f < 2; f++) {
            uint32_t y[4];
#pragma unroll
            for (int b = 0; b < 4; b++) {
              const int i = ((c & 1) * 4 + b) * 4 + 2 * f;
              y[b] = pack_bf16(swiglu(acc[c >> 1][i], acc[c >> 1][i] * acc[c >> 1][32 + i]), swiglu(acc[c >> 1][i + 1], acc[c >> 1][i + 1] * acc[c >> 1][33 + i]));
            }
            stg128(tile + img_pos(w, lane) + ((c >> 1) ^ rank) * 512 + (c & 1) * 256 + f * 32, y[0], y[1], y[2], y[3]);
            if (c + f < 4) until(ts, (2 * c + f + 1) * P_ACT);
            fence_regs(acc[0]); fence_regs(acc[1]);
          }
        if (T == 0) {
          if (wg == 0 && j < N_HK) publish(ld_relaxed(tile + img_line(w, lane)), cnt + G_HK, 1);
          mbar_wait(bars + (px_y & 0x3ff), 1);
          uint32_t z[16];
#pragma unroll
          for (int i = 0; i < 4; i++) { const uint4 x = lds128(bars - 8192 + (tid_now() & 127) * 16 + i * 2048); z[4 * i] = x.x; z[4 * i + 1] = x.y; z[4 * i + 2] = x.z; z[4 * i + 3] = x.w; }
          landed(z[0] & z[4] & z[8] & z[12]);
          named_sync(1 + wg, 128);
          pp.release(px_y);
#pragma unroll
          for (int c = 0; c < 2; c++)
#pragma unroll
            for (int f = 0; f < 2; f++) {
              uint32_t y[4];
#pragma unroll
              for (int b = 0; b < 4; b++) {
                const int i = (c * 4 + b) * 2 + f;
                const float o0 = bf_lo(z[i]), o1 = bf_hi(z[i]);
                y[b] = pack_bf16(swiglu(rank ? o0 : ax[2 * i], o0 * ax[2 * i]), swiglu(rank ? o1 : ax[2 * i + 1], o1 * ax[2 * i + 1]));
              }
              stg128(tx + img_pos(w, lane) + c * 256 + f * 32, y[0], y[1], y[2], y[3]);
            }
        }
        seen = ld_relaxed(tile + img_line(w, lane));
        seen2 = ld_relaxed(tx + img_line(w, lane & 15));
      }
      if (T == 2) break;
      const int n0 = 45 + 16 * T, n1 = n0 + 16;
#pragma unroll 1
      for (int n = n0; n < n1; n++) {
        const uint2 e = pp.begin(n);
        const uint32_t da = e.x & 0xffff, db = dB0 + (e.x >> 16);
        wg_fence();
#pragma unroll
        for (int q = 0; q < 4; q++) {
          wg_n128<H64, H128>(acc[0], dAo + da + qa(q), db + 128 * q, q ? 1 : n - n0);
          wg_n128<H64, H128>(acc[1], dAp + da + qa(q), db + 128 * q, q ? 1 : n - n0);
        }
        wg_commit();
        if (n == n0 + 1) publish(opaque(seen) & opaque(seen2), cnt + G_ACT + T, 1);
        pp.end(e.y);
      }
    }
    {
      float gf[32];
#pragma unroll
      for (int ph = 0; ph < 2; ph++) {
#pragma unroll 1
        for (int n = ph ? 90 : 77; n < (ph ? N_END : 90); n++) {
          const uint2 e = pp.begin(n);
          const uint32_t da = dA0 + wg * 512 + (e.x & 0xffff), db = dB0 + (e.x >> 16);
          wg_fence();
#pragma unroll
          for (int q = 0; q < 4; q++) wg_n128<H64, H128>(acc[0], da + qa(q), db + 128 * q, q || ph ? 1 : n - 77);
          wg_commit();
          pp.end(e.y);
        }
        if (ph == 0) {
          publish(opaque(seen) & opaque(seen2), cnt + G_ACT + 2, 1);
          mbar_wait(bars + B_GB, 0);
#pragma unroll
          for (int i = 0; i < 4; i++) {
            const uint4 x = lds128(sb + PAR_OFF + 768 + (tid_now() & 3) * 64 + i * 16);
            const uint32_t g4[4] = {x.x, x.y, x.z, x.w};
#pragma unroll
            for (int b = 0; b < 4; b++) { gf[8 * i + 2 * b] = bf_lo(g4[b]); gf[8 * i + 2 * b + 1] = bf_hi(g4[b]); }
          }
          fence_regs(gf);
        }
      }
      const uint32_t lane = tid_now() & 31;
      {
        const uint2 e0 = pp.begin(N_END), e1 = pp.begin(N_END + 1);
#pragma unroll
        for (int i = 0; i < 8; i++) {
          const uint4 r = lds128(sb + (((i & 4 ? e1.x : e0.x) & 0xffff) + wg * 512 + img_pos(w, lane) + ((i >> 1) & 1) * 256 + (i & 1) * 32) * 16);
          const uint32_t x[4] = {r.x, r.y, r.z, r.w};
#pragma unroll
          for (int b = 0; b < 4; b++) { acc[1][(i >> 1) * 16 + 4 * b + 2 * (i & 1)] = bf_lo(x[b]); acc[1][(i >> 1) * 16 + 4 * b + 2 * (i & 1) + 1] = bf_hi(x[b]); }
        }
      }
      const uint32_t st = sb + ((w & 2) ? pp.nx.x >> 16 : pp.nx.x & 0xffff) * 16 + wg * 8192 + (w & 1) * 4096;
      const uint32_t a0 = opaque(st + (lane & 15) * 128 + (((lane >> 4) ^ (lane & 7)) << 4));
      if (pp.lead && elect_one()) mbar_arrive(bars + B_END);
      wg_wait<0>();
      pp.release_now(pp.prev);
      fence_regs(acc[0]);
#pragma unroll
      for (int c = 0; c < 4; c++) {
        uint32_t y[2][4];
#pragma unroll
        for (int f = 0; f < 2; f++)
#pragma unroll
          for (int b = 0; b < 4; b++) {
            const int i = 16 * c + 4 * b + 2 * f;
            y[f][b] = pack_bf16(fmaf(gf[8 * c + 2 * b], acc[0][i], acc[1][i]), fmaf(gf[8 * c + 2 * b + 1], acc[0][i + 1], acc[1][i + 1]));
          }
        stsm4((a0 ^ ((c & 1) << 6)) + (c >> 1) * 2048, y[0][0], y[1][0], y[0][1], y[1][1]);
        stsm4((a0 ^ ((c & 1) << 6) ^ 32) + (c >> 1) * 2048, y[0][2], y[1][2], y[0][3], y[1][3]);
        if (c == 1) {
          fence_async_smem(); __syncwarp();
          if (elect_one()) {
            tma2d_st(&P.mOut, st, typ * D_ + (j & 7) * 128, grp * 128 + wg * 64 + w * 16);
            bulk_commit();
          }
        }
      }
      {
        __syncwarp();
        const uint32_t ln = tid_now() & 31;
        uint4* op = (uint4*)(Q.out + (size_t)(grp * 256 + 2 * (wg * 64 + w * 16 + (ln >> 3)) + typ) * D_ + (j & 7) * 128 + 64) + (ln & 7);
        uint4 r[4];
#pragma unroll
        for (int k = 0; k < 4; k++) r[k] = lds128(st + 2048 + ((ln >> 3) + 4 * k) * 128 + (((ln & 7) ^ (((ln >> 3) + 4 * k) & 7)) << 4));
#pragma unroll
        for (int k = 0; k < 4; k++) stg128(op + k * D_, r[k].x, r[k].y, r[k].z, r[k].w);
        if (elect_one()) bulk_wait_read();
      }
    }
  } else {
    asm volatile("setmaxnreg.dec.sync.aligned.u32 40;");
    const uint32_t lane = tid_now() & 31;
    if (elect_one()) {
      if (warp == 10) {
        prefetch_tmap(&P.mWqkv);
#pragma unroll
        for (int i = 0; i < 12; i++) mbar_init(bars + 1024 + 8 * i, i < 4 ? 4 : 1);
        mbar_init(bars + B_ST, 4); mbar_init(bars + B_ST + 8, 8); mbar_init(bars + B_XB, 1); mbar_init(bars + B_XB + 8, 1); mbar_init(bars + B_END, 2);
        sts32(bars + ROLE_OFF, cta >> 1);
      } else if (warp == 11) {
#pragma unroll 1
        for (int u = 0; u < 2; u++) {
#pragma unroll
          for (int i = 0; i < 20; i++) mbar_init(bars + u * 512 + 352 + 8 * i, 1 + u);
        }
      } else {
#pragma unroll 22
        for (int i = 0; i < 44; i++) mbar_init(bars + (warp & 1) * 512 + 8 * i, 1 + (warp & 1));
      }
      asm volatile("fence.mbarrier_init.release.cluster;" ::: "memory");
    }
    named_sync(0, NTHREADS);
    asm volatile("barrier.cluster.arrive.relaxed.aligned;" ::: "memory");
    asm volatile("barrier.cluster.wait.aligned;" ::: "memory");
    const uint32_t ep0 = ld_relaxed(&Q.s->ep[cta * 32 + lane]);
    if (!(warp & 1)) {
      if (only_one()) {
        const int q = (warp >> 1) & 1;
        const uint2* tab = c_act[q];
        const char* src = (const char*)(Q.s->img + (size_t)grp * (N_TILES * 1024) + rank * 512);
        const uint32_t sa = sb + rank * 8192;
        if (q) {
          if (cta >= 64) {
#pragma unroll 1
            for (int i = 0; i < 4; i++) {
              until(t0, (cta >= 96 ? T_Q3 : T_Q2) + i * P_Q);
              mbar_expect_tx(bars + B_SL + 8 * i, 8192);
              tma2d_once(sb + SL_OFF + i * 8192, &P.mWm2, bars + B_SL + 8 * i, ((cta >> 4) & 1) * D_ + (cta >> 5) * 256 + ((cta >> 2) & 3) * 64, (cta & 3) * 256 + i * 64);
            }
          }
        }
        mbar_expect_tx(bars + B_XB + 8 * q, 16384);
#pragma unroll 1
        for (int i = 0; i < 8; i++) {
          until(t0, q ? T_XB + i * P_XB : T_XA);
          bulk_g2s(sb + (4 + q) * 16384 + i * 2048, Q.x + (size_t)(cta * 16 + 2 * i + q) * D_, 2048, bars + B_XB + 8 * q);
        }
        const uint32_t target = (opaque(ep0) + 1) * 64;
        const uint32_t* cnt = Q.s->cnt + grp * 32;
        const char* x1 = src + (T_X1 + typ * 16 + (j & 7) * 2) * 16384 + (q - rank) * 8192;
        uint2 nx = tab[0];
#pragma unroll 1
        for (int ph = 0; ph < 4; ph++) {
          const bool half = ph == 3;
          tiles<1>(bars, tab, nx, half ? 77 : (ph ? 11 + 17 * ph : 0), half ? N_END : (ph ? 11 + 33 * ph : 16), half ? sb + q * 8192 + rank * 4096 : sa,
                   half ? src + typ * 56 * 16384 + q * 8192 - rank * 4096 : src, half ? 4096 : 8192, half ? cnt + typ * 8 : cnt, target, 0, 0);
          if (ph == 1) { mbar_expect_tx(bars + (nx.y & 0x3ff), 8192); nx = tab[45]; }
          if (ph) continue;
#pragma unroll 1
          for (int n = 16; n < 28; n++) {
            const uint2 e = nx;
            nx = tab[n + 1];
            const uint32_t fb = bars + (e.y & 0x3ff);
            mbar_wait(bars + (e.x & 0x7ff), e.x >> 31);
            mbar_expect_tx(fb, (e.y >> 29) << 13);
            if (n == 17) {
              tma2d(sb + (e.y & 0x3c000), &P.mX, fb, q * D_ + (j & 14) * 64, grp * 128 + rank * 64);
              tma2d(sb + (e.y & 0x3c000) + 8192, &P.mX, fb, q * D_ + (j | 1) * 64, grp * 128 + rank * 64);
              tiles<0>(bars, tab, nx, 18, 26, sb, src + rank * 8192, 16384, cnt, target, q ? P_G2B : P_G2, q ? F_G2B : F_G2A);
              n = 25;
            }
          }
        }
        while ((int32_t)(ld_relaxed_line(cnt + G_X1) - target) < 0) {}
        asm volatile("fence.acquire.gpu;" ::: "memory"); fence_async_glob();
#pragma unroll 1
        for (int n = 0; n < 2; n++) {
          const uint2 e = tab[N_END + n];
          const uint32_t fb = bars + (e.y & 0x3ff);
          mbar_expect_tx(fb, 8192);
          mbar_wait(bars + (e.x & 0x7ff), e.x >> 31);
          bulk_g2s(sb + q * 8192 + (e.y & 0x3c000), x1 + n * 16384, 8192, fb);
        }
      }
    } else if (warp == 9) {
      if (only_one()) {
        uint2 nx = c_w[0][0];
#pragma unroll 1
        for (int n = 0; n < N_W;) {
          if (n < 5) until(t0, n ? T_W + (n - 1) * P_W : T_W0);
          if (n == 2) mbar_wait(bars + B_SLE, 0);
          if (n == 5) { prefetch_tmap(&P.mWo); prefetch_tmap(&P.mWg); prefetch_tmap(&P.mWu); prefetch_tmap(&P.mWd); prefetch_tmap(&P.mX); }
          const int u = (nx.y >> 10) & 7;
          if (u < 2) {
            weights<3>(sb, nx, n, u ? &P.mWg : &P.mWqkv, u ? &P.mWu : &P.mWqkv, u ? &P.mWg + rank : &P.mWqkv,
                       j * 64, (u ? 0 : D_) + j * 64, u ? 1024 + (j >> 1) * 64 : 2 * D_ + j * 64, 0);
          } else {
            const bool ffn = u == 3 || u == 4;
            const int c0 = ffn ? u * 1024 - 1536 + j * 64 : (u == 2 ? j >> 1 : j & 7) * 128;
            const CUtensorMap* m0 = ffn ? &P.mWg : (u == 2 ? &P.mWo : &P.mWd);
            weights<2>(sb, nx, n, m0, m0 + ffn, nullptr, c0, ffn ? c0 : c0 + 64, 0, u == 2 ? rank * 2 : 0);
          }
        }
        prefetch_tmap(&P.mOut);
      }
    } else {
      {
        const uint32_t i = opaque((grp * 2 + rank) * 8), k = i < N_W - 128 ? i + 128 : 128;
        if ((c_cons[0][i].x & c_cons[1][i].x & c_act[0][i].y & c_act[1][i].y & c_w[0][i].y & c_w[0][k].y) == 0xffffffffu) __trap();
      }
      const uint32_t ep = opaque(ep0) + 1;
      if (lane == 0) {
        sts32(bars + ROLE_OFF + 4, ep);
        uint32_t pr; asm volatile("ld.shared::cluster.u32 %0, [%1];" : "=r"(pr) : "r"(mapa(bars + ROLE_OFF, rank ^ 1)) : "memory");
        if (pr != (uint32_t)(cta >> 1) || sb != smem_u32(smem_raw)) { __trap(); }
      }
      const uint32_t tag = tag_of(ep);
#pragma unroll 1
      for (int i = 0; i < 8; i++) {
        const uint2* src = (const uint2*)(Q.s->modp + (i >> 1) * 1024 + (i < 6 ? j >> 1 : j & 7) * 128 + (i & 1) * 64) + lane;
        uint2 a; uint32_t it = 0;
        do { if (it) __nanosleep(200); a = ld_relaxed_b64(src); guard(++it); } while (__any_sync(~0u, ((a.x ^ tag) | (a.y ^ tag)) & 3u));
        uint32_t p = pack_bf16(__uint_as_float(a.x), __uint_as_float(a.y));
        if ((i >> 1) == 2) p = pack_bf16(1.f + bf_lo(p), 1.f + bf_hi(p));
        const float sc = i < 2 ? 1.f : (i < 6 ? 0.5f : 2.f);
        p = pack_bf16(sc * bf_lo(p), sc * bf_hi(p));
        sts32(sb + PAR_OFF + (i >> 1) * 256 + (lane & 3) * 64 + (i & 1) * 32 + (lane >> 2) * 4, p);
        __syncwarp();
        if ((i == 1 || i == 5 || i == 7) && elect_one()) { mbar_arrive(bars + (i == 7 ? B_GB : B_PAR + (i & 4) * 2)); }
      }
      mbar_wait_bounded(bars + B_R, 0);
      Q.s->ep[cta * 32 + lane] = ep;
      mbar_wait_bounded(bars + B_END, 0);
    }
  }
}

typedef CUresult (*PFN_encodeTiled)(CUtensorMap*, CUtensorMapDataType, cuuint32_t, void*, const cuuint64_t*, const cuuint64_t*,
                                    const cuuint32_t*, const cuuint32_t*, CUtensorMapInterleave, CUtensorMapSwizzle,
                                    CUtensorMapL2promotion, CUtensorMapFloatOOBfill);

void make_map(PFN_encodeTiled enc, CUtensorMap* m, const void* ptr, uint64_t inner, uint64_t outer, uint32_t box_outer, int promo = CU_TENSOR_MAP_L2_PROMOTION_L2_256B) {
  cuuint64_t dims[2] = {inner, outer};
  cuuint64_t strides[1] = {inner * 2};
  cuuint32_t box[2] = {64, box_outer};
  cuuint32_t es[2] = {1, 1};
  enc(m, CU_TENSOR_MAP_DATA_TYPE_BFLOAT16, 2, const_cast<void*>(ptr), dims, strides, box, es, CU_TENSOR_MAP_INTERLEAVE_NONE,
      CU_TENSOR_MAP_SWIZZLE_128B, (CUtensorMapL2promotion)promo, CU_TENSOR_MAP_FLOAT_OOB_FILL_NONE);
}
void make_wmap(PFN_encodeTiled enc, CUtensorMap* m, const void* ptr, uint64_t cols, uint64_t rows, bool permuted) {
  cuuint64_t dims[5] = {cols, 2, 4, 4, rows / 32};
  cuuint64_t strides[4] = {cols * 2, cols * 2 * (permuted ? 8 : 2), cols * 2 * (permuted ? 2 : 8), cols * 2 * 32};
  cuuint32_t box[5] = {64, 2, 4, 4, 2};
  cuuint32_t es[5] = {1, 1, 1, 1, 1};
  enc(m, CU_TENSOR_MAP_DATA_TYPE_BFLOAT16, 5, const_cast<void*>(ptr), dims, strides, box, es, CU_TENSOR_MAP_INTERLEAVE_NONE,
      CU_TENSOR_MAP_SWIZZLE_128B, CU_TENSOR_MAP_L2_PROMOTION_L2_128B, CU_TENSOR_MAP_FLOAT_OOB_FILL_NONE);
}

}

extern "C" void kernel_launch(void* const* d_in, const int* in_sizes, int n_in, void* d_out, int out_size) {
  (void)in_sizes; (void)n_in; (void)out_size;
  static PFN_encodeTiled enc = nullptr;
  static void* scratch = nullptr;
  static int sms = 0;
  if (!enc) {
    int dev = 0;
    cudaGetDevice(&dev);
    cudaDeviceGetAttribute(&sms, cudaDevAttrMultiProcessorCount, dev);
    cudaGetSymbolAddress(&scratch, g_s);
    void* fn = nullptr;
    cudaDriverEntryPointQueryResult q;
    cudaGetDriverEntryPoint("cuTensorMapEncodeTiled", &fn, cudaEnableDefault, &q);
    enc = (PFN_encodeTiled)fn;
    cudaFuncSetAttribute(fused_kernel<true>, cudaFuncAttributeMaxDynamicSharedMemorySize, SMEM_BYTES);
    cudaFuncSetAttribute(fused_kernel<false>, cudaFuncAttributeMaxDynamicSharedMemorySize, SMEM_BYTES);
  }
  Params P;
  make_wmap(enc, &P.mWqkv, d_in[1], 3 * D_, D_, false);
  make_wmap(enc, &P.mWo, d_in[2], D_, D_, true);
  make_wmap(enc, &P.mWg, d_in[4], F_, D_, true);
  make_wmap(enc, &P.mWu, d_in[5], F_, D_, true);
  make_wmap(enc, &P.mWd, d_in[6], D_, F_, true);
  make_map(enc, &P.mOut, d_out, 2 * D_, S_ / 2, 16);
  make_map(enc, &P.mX, d_in[0], 2 * D_, S_ / 2, 64, CU_TENSOR_MAP_L2_PROMOTION_L2_128B);
  make_map(enc, &P.mWm2, d_in[8], 6 * D_, D_, 64, CU_TENSOR_MAP_L2_PROMOTION_L2_128B);
  Ptrs Q;
  Q.s = (Scratch*)scratch;
  Q.x = (const __nv_bfloat16*)d_in[0];
  Q.c = (const __nv_bfloat16*)d_in[7];
  Q.out = (__nv_bfloat16*)d_out;
  if (sms == NCTA + 4) fused_kernel<true><<<NCTA + 4, NTHREADS, SMEM_BYTES, cudaStreamPerThread>>>(Q, P);
  else fused_kernel<false><<<NCTA + 4, NTHREADS, SMEM_BYTES, cudaStreamPerThread>>>(Q, P);
}
```

```cpp
#include <cuda_runtime.h>
#include <cuda.h>
#include <cuda_bf16.h>
#include <stdint.h>
#include <stddef.h>
#include <string.h>
#include <math.h>

template <uint32_t HA, uint32_t HB> __device__ __forceinline__ void wg_n128(float (&d)[64], uint32_t descA, uint32_t descB, int scaleD) {
  asm volatile("{\n.reg .pred p;\n.reg .b64 da, db;\n"
    "mov.b64 da, {%64, %67};\nmov.b64 db, {%65, %68};\n"
    "setp.ne.b32 p, %66, 0;\n"
    "wgmma.mma_async.sync.aligned.m64n128k16.f32.bf16.bf16 "
    "{%0, %1, %2, %3, %4, %5, %6, %7, %8, %9, %10, %11, %12, %13, %14, %15, "
    "%16, %17, %18, %19, %20, %21, %22, %23, %24, %25, %26, %27, %28, %29, %30, %31, "
    "%32, %33, %34, %35, %36, %37, %38, %39, %40, %41, %42, %43, %44, %45, %46, %47, "
    "%48, %49, %50, %51, %52, %53, %54, %55, %56, %57, %58, %59, %60, %61, %62, %63}, "
    "da, db, p, 1, 1, 0, 1;\n}\n"
    : "+f"(d[0]), "+f"(d[1]), "+f"(d[2]), "+f"(d[3]), "+f"(d[4]), "+f"(d[5]), "+f"(d[6]), "+f"(d[7]),
      "+f"(d[8]), "+f"(d[9]), "+f"(d[10]), "+f"(d[11]), "+f"(d[12]), "+f"(d[13]), "+f"(d[14]), "+f"(d[15]),
      "+f"(d[16]), "+f"(d[17]), "+f"(d[18]), "+f"(d[19]), "+f"(d[20]), "+f"(d[21]), "+f"(d[22]), "+f"(d[23]),
      "+f"(d[24]), "+f"(d[25]), "+f"(d[26]), "+f"(d[27]), "+f"(d[28]), "+f"(d[29]), "+f"(d[30]), "+f"(d[31]),
      "+f"(d[32]), "+f"(d[33]), "+f"(d[34]), "+f"(d[35]), "+f"(d[36]), "+f"(d[37]), "+f"(d[38]), "+f"(d[39]),
      "+f"(d[40]), "+f"(d[41]), "+f"(d[42]), "+f"(d[43]), "+f"(d[44]), "+f"(d[45]), "+f"(d[46]), "+f"(d[47]),
      "+f"(d[48]), "+f"(d[49]), "+f"(d[50]), "+f"(d[51]), "+f"(d[52]), "+f"(d[53]), "+f"(d[54]), "+f"(d[55]),
      "+f"(d[56]), "+f"(d[57]), "+f"(d[58]), "+f"(d[59]), "+f"(d[60]), "+f"(d[61]), "+f"(d[62]), "+f"(d[63])
    : "r"(descA), "r"(descB), "r"(scaleD), "n"(HA), "n"(HB));
}
template <uint32_t HA, uint32_t HB> __device__ __forceinline__ void wg_n192(float (&d)[96], uint32_t descA, uint32_t descB, int scaleD) {
  asm volatile("{\n.reg .pred p;\n.reg .b64 da, db;\n"
    "mov.b64 da, {%96, %99};\nmov.b64 db, {%97, %100};\n"
    "setp.ne.b32 p, %98, 0;\n"
    "wgmma.mma_async.sync.aligned.m64n192k16.f32.bf16.bf16 "
    "{%0, %1, %2, %3, %4, %5, %6, %7, %8, %9, %10, %11, %12, %13, %14, %15, "
    "%16, %17, %18, %19, %20, %21, %22, %23, %24, %25, %26, %27, %28, %29, %30, %31, "
    "%32, %33, %34, %35, %36, %37, %38, %39, %40, %41, %42, %43, %44, %45, %46, %47, "
    "%48, %49, %50, %51, %52, %53, %54, %55, %56, %57, %58, %59, %60, %61, %62, %63, "
    "%64, %65, %66, %67, %68, %69, %70, %71, %72, %73, %74, %75, %76, %77, %78, %79, "
    "%80, %81, %82, %83, %84, %85, %86, %87, %88, %89, %90, %91, %92, %93, %94, %95}, "
    "da, db, p, 1, 1, 0, 1;\n}\n"
    : "+f"(d[0]), "+f"(d[1]), "+f"(d[2]), "+f"(d[3]), "+f"(d[4]), "+f"(d[5]), "+f"(d[6]), "+f"(d[7]),
      "+f"(d[8]), "+f"(d[9]), "+f"(d[10]), "+f"(d[11]), "+f"(d[12]), "+f"(d[13]), "+f"(d[14]), "+f"(d[15]),
      "+f"(d[16]), "+f"(d[17]), "+f"(d[18]), "+f"(d[19]), "+f"(d[20]), "+f"(d[21]), "+f"(d[22]), "+f"(d[23]),
      "+f"(d[24]), "+f"(d[25]), "+f"(d[26]), "+f"(d[27]), "+f"(d[28]), "+f"(d[29]), "+f"(d[30]), "+f"(d[31]),
      "+f"(d[32]), "+f"(d[33]), "+f"(d[34]), "+f"(d[35]), "+f"(d[36]), "+f"(d[37]), "+f"(d[38]), "+f"(d[39]),
      "+f"(d[40]), "+f"(d[41]), "+f"(d[42]), "+f"(d[43]), "+f"(d[44]), "+f"(d[45]), "+f"(d[46]), "+f"(d[47]),
      "+f"(d[48]), "+f"(d[49]), "+f"(d[50]), "+f"(d[51]), "+f"(d[52]), "+f"(d[53]), "+f"(d[54]), "+f"(d[55]),
      "+f"(d[56]), "+f"(d[57]), "+f"(d[58]), "+f"(d[59]), "+f"(d[60]), "+f"(d[61]), "+f"(d[62]), "+f"(d[63]),
      "+f"(d[64]), "+f"(d[65]), "+f"(d[66]), "+f"(d[67]), "+f"(d[68]), "+f"(d[69]), "+f"(d[70]), "+f"(d[71]),
      "+f"(d[72]), "+f"(d[73]), "+f"(d[74]), "+f"(d[75]), "+f"(d[76]), "+f"(d[77]), "+f"(d[78]), "+f"(d[79]),
      "+f"(d[80]), "+f"(d[81]), "+f"(d[82]), "+f"(d[83]), "+f"(d[84]), "+f"(d[85]), "+f"(d[86]), "+f"(d[87]),
      "+f"(d[88]), "+f"(d[89]), "+f"(d[90]), "+f"(d[91]), "+f"(d[92]), "+f"(d[93]), "+f"(d[94]), "+f"(d[95])
    : "r"(descA), "r"(descB), "r"(scaleD), "n"(HA), "n"(HB));
}
template <uint32_t HA, uint32_t HB> __device__ __forceinline__ void wg_n256(float (&d)[128], uint32_t descA, uint32_t descB, int scaleD) {
  asm volatile("{\n.reg .pred p;\n.reg .b64 da, db;\n"
    "mov.b64 da, {%128, %131};\nmov.b64 db, {%129, %132};\n"
    "setp.ne.b32 p, %130, 0;\n"
    "wgmma.mma_async.sync.aligned.m64n256k16.f32.bf16.bf16 "
    "{%0, %1, %2, %3, %4, %5, %6, %7, %8, %9, %10, %11, %12, %13, %14, %15, "
    "%16, %17, %18, %19, %20, %21, %22, %23, %24, %25, %26, %27, %28, %29, %30, %31, "
    "%32, %33, %34, %35, %36, %37, %38, %39, %40, %41, %42, %43, %44, %45, %46, %47, "
    "%48, %49, %50, %51, %52, %53, %54, %55, %56, %57, %58, %59, %60, %61, %62, %63, "
    "%64, %65, %66, %67, %68, %69, %70, %71, %72, %73, %74, %75, %76, %77, %78, %79, "
    "%80, %81, %82, %83, %84, %85, %86, %87, %88, %89, %90, %91, %92, %93, %94, %95, "
    "%96, %97, %98, %99, %100, %101, %102, %103, %104, %105, %106, %107, %108, %109, %110, %111, "
    "%112, %113, %114, %115, %116, %117, %118, %119, %120, %121, %122, %123, %124, %125, %126, %127}, "
    "da, db, p, 1, 1, 0, 1;\n}\n"
    : "+f"(d[0]), "+f"(d[1]), "+f"(d[2]), "+f"(d[3]), "+f"(d[4]), "+f"(d[5]), "+f"(d[6]), "+f"(d[7]),
      "+f"(d[8]), "+f"(d[9]), "+f"(d[10]), "+f"(d[11]), "+f"(d[12]), "+f"(d[13]), "+f"(d[14]), "+f"(d[15]),
      "+f"(d[16]), "+f"(d[17]), "+f"(d[18]), "+f"(d[19]), "+f"(d[20]), "+f"(d[21]), "+f"(d[22]), "+f"(d[23]),
      "+f"(d[24]), "+f"(d[25]), "+f"(d[26]), "+f"(d[27]), "+f"(d[28]), "+f"(d[29]), "+f"(d[30]), "+f"(d[31]),
      "+f"(d[32]), "+f"(d[33]), "+f"(d[34]), "+f"(d[35]), "+f"(d[36]), "+f"(d[37]), "+f"(d[38]), "+f"(d[39]),
      "+f"(d[40]), "+f"(d[41]), "+f"(d[42]), "+f"(d[43]), "+f"(d[44]), "+f"(d[45]), "+f"(d[46]), "+f"(d[47]),
      "+f"(d[48]), "+f"(d[49]), "+f"(d[50]), "+f"(d[51]), "+f"(d[52]), "+f"(d[53]), "+f"(d[54]), "+f"(d[55]),
      "+f"(d[56]), "+f"(d[57]), "+f"(d[58]), "+f"(d[59]), "+f"(d[60]), "+f"(d[61]), "+f"(d[62]), "+f"(d[63]),
      "+f"(d[64]), "+f"(d[65]), "+f"(d[66]), "+f"(d[67]), "+f"(d[68]), "+f"(d[69]), "+f"(d[70]), "+f"(d[71]),
      "+f"(d[72]), "+f"(d[73]), "+f"(d[74]), "+f"(d[75]), "+f"(d[76]), "+f"(d[77]), "+f"(d[78]), "+f"(d[79]),
      "+f"(d[80]), "+f"(d[81]), "+f"(d[82]), "+f"(d[83]), "+f"(d[84]), "+f"(d[85]), "+f"(d[86]), "+f"(d[87]),
      "+f"(d[88]), "+f"(d[89]), "+f"(d[90]), "+f"(d[91]), "+f"(d[92]), "+f"(d[93]), "+f"(d[94]), "+f"(d[95]),
      "+f"(d[96]), "+f"(d[97]), "+f"(d[98]), "+f"(d[99]), "+f"(d[100]), "+f"(d[101]), "+f"(d[102]), "+f"(d[103]),
      "+f"(d[104]), "+f"(d[105]), "+f"(d[106]), "+f"(d[107]), "+f"(d[108]), "+f"(d[109]), "+f"(d[110]), "+f"(d[111]),
      "+f"(d[112]), "+f"(d[113]), "+f"(d[114]), "+f"(d[115]), "+f"(d[116]), "+f"(d[117]), "+f"(d[118]), "+f"(d[119]),
      "+f"(d[120]), "+f"(d[121]), "+f"(d[122]), "+f"(d[123]), "+f"(d[124]), "+f"(d[125]), "+f"(d[126]), "+f"(d[127])
    : "r"(descA), "r"(descB), "r"(scaleD), "n"(HA), "n"(HB));
}

namespace {

constexpr int S_ = 2048, D_ = 1024, F_ = 3584;
constexpr int NCTA = 128;
constexpr int NTHREADS = 384;

constexpr uint32_t W_OFF      = 6 * 16384;
constexpr uint32_t BAR_OFF    = W_OFF + 16 * 8192;
constexpr uint32_t PAR_OFF    = BAR_OFF + 1280;
constexpr uint32_t SMEM_BYTES = 232448, SMEM_BASE = 1024;
constexpr uint32_t SL_OFF     = W_OFF + 11 * 8192;
constexpr uint32_t TAB_OFF    = W_OFF + 15 * 8192;
constexpr uint32_t B_R = 1024, B_PAR = 1072, B_SL = 1120, B_SLE = 1088, B_Q = 1096, B_ST = 1152, B_GB = 1056, B_XB = 1168, B_END = 1184, ROLE_OFF = 1272;

constexpr uint32_t H128 = 0x40000040u;
constexpr uint32_t H64  = 0x80000020u;

constexpr int N_W = 137, N_HK = 3, N_END = 130;
__constant__ uint2 c_cons[2][135] = {
  {
    {0x0,0x84580800}, {0x6000400,0x84580808}, {0x18000800,0x84580810}, {0x12000c00,0x84580818}, {0xc001000,0x84580820}, {0x0,0x84580828},
    {0x6000400,0x84580830}, {0x18000800,0x84580838}, {0x12000c00,0x84580840}, {0xc000000,0x84580848}, {0x800,0x84580850}, {0x6000c00,0x84580858},
    {0x18000000,0x84580860}, {0x12000800,0x84580868}, {0xc000c00,0x84580870}, {0x0,0x84580878}, {0x400,0x84580880}, {0x400,0x84580888},
    {0x18001000,0x4500890}, {0x1c000000,0x84580898}, {0x14000800,0x845818a0}, {0xc001400,0x41008a8}, {0x10000c00,0x845818b0}, {0x1000,0x41808b8},
    {0x4000000,0x845808c0}, {0x8000800,0x845808c8}, {0x1400,0x845808d0}, {0x1400,0x845808d8}, {0x18000000,0x3b808e0}, {0xc000800,0x845808e8},
    {0x12001400,0x845808f0}, {0xc00,0x845808f8}, {0x6001000,0x84580c00}, {0x18000400,0x84580c08}, {0xc000000,0x84580c10}, {0x12000800,0x84580c18},
    {0xc00,0x84580c20}, {0x6000400,0x84580c28}, {0x18000800,0x84580c30}, {0xc000c00,0x84580c38}, {0x12000400,0x84580c40}, {0x800,0x84580c48},
    {0x6000c00,0x84580c50}, {0x18000400,0x84580c58}, {0x0,0x3d80c60}, {0x14001400,0x83500c68}, {0xc00,0x84580c70}, {0x4001000,0x84580c78},
    {0x8000400,0x84580c80}, {0x18000000,0x84580c88}, {0xc000800,0x84580c90}, {0x10000c00,0x84580c98}, {0x1c000400,0x84580ca0}, {0x14000800,0x84580ca8},
    {0xc00,0x84580cb0}, {0x4000400,0x84580cb8}, {0x8000800,0x84580cc0}, {0x18000c00,0x84580cc8}, {0xc000400,0x84580cd0}, {0x10000800,0x84580cd8},
    {0x1c000c00,0x84580ce0}, {0x14001000,0x83d80ce8}, {0x400,0x84580cf0}, {0x4000000,0x84580cf8}, {0x8000800,0x84580800}, {0x18001400,0x84580808},
    {0xc000c00,0x84580810}, {0x10000400,0x84580818}, {0x1c000800,0x84580820}, {0x14000c00,0x84580828}, {0x400,0x84580830}, {0x4000800,0x84580838},
    {0x8000c00,0x84580840}, {0x18000400,0x84580848}, {0xc000800,0x84580850}, {0x10000c00,0x84580858}, {0x1c000400,0x84580860}, {0x14000000,0x3580868},
    {0x800,0x84580870}, {0x4001400,0x84580878}, {0x8000c00,0x84580880}, {0x18001000,0x84580888}, {0xc000400,0x84580890}, {0x10000000,0x84580898},
    {0x1c000800,0x845808a0}, {0x14001400,0x845808a8}, {0xc00,0x845808b0}, {0x4001000,0x845808b8}, {0x8000400,0x845808c0}, {0x18000000,0x845808c8},
    {0xc000800,0x845808d0}, {0x10001400,0x845808d8}, {0x1c000c00,0x845808e0}, {0x14001000,0x845808e8}, {0x400,0x845808f0}, {0x4000000,0x845808f8},
    {0x8000800,0x84580c00}, {0x18001400,0x84580c08}, {0xc000c00,0x84580c10}, {0x10001000,0x84580c18}, {0x1c000400,0x84580c20}, {0x14000000,0x84580c28},
    {0x800,0x84580c30}, {0x4001400,0x84580c38}, {0x8000c00,0x84580c40}, {0x18001000,0x84580c48}, {0xc000400,0x84580c50}, {0x10000000,0x84580c58},
    {0x1c000800,0x84580c60}, {0x14001400,0x84580c68}, {0xc00,0x84580c70}, {0x4001000,0x84580c78}, {0x8000400,0x84580c80}, {0x18000000,0x84580c88},
    {0xc000800,0x84580c90}, {0x10001400,0x84580c98}, {0x1c000c00,0x84580ca0}, {0x14001000,0x84580ca8}, {0x400,0x84580cb0}, {0x4000000,0x84580cb8},
    {0x8000800,0x84580cc0}, {0x18001400,0x84580cc8}, {0xc000c00,0x84580cd0}, {0x10001000,0x84580cd8}, {0x1c000400,0x84580ce0}, {0x14000000,0x84580ce8},
    {0x800,0x84580cf0}, {0x4001400,0x84580cf8}, {0x8000c00,0x84580800}, {0x18001000,0x84580808}, {0x400,0x84580010}, {0x0,0x84580018},
    {0x14000800,0x0}, {0x14000800,0x0}, {0x14000800,0x0},
  },
  {
    {0x6001400,0x300900}, {0x18001000,0x380908}, {0x12000400,0x400910}, {0xc001400,0x480918}, {0x1000,0x500920}, {0x6000400,0x580928},
    {0x18001400,0x600930}, {0x12001000,0x680938}, {0xc000800,0x4480940}, {0x1400,0x84581948}, {0x6000c00,0x4001950}, {0x18001000,0x4080958},
    {0x12000000,0x84580960}, {0xc000800,0x84580968}, {0x1400,0x84580970}, {0x6000c00,0x84580978}, {0x400,0x84580980}, {0x400,0x84580988},
    {0x18000c00,0x2b80990}, {0x1c001000,0x84580998}, {0x14000400,0x845809a0}, {0xc000000,0x845809a8}, {0x10000800,0x845809b0}, {0x1400,0x845809b8},
    {0x4000c00,0xc009c0}, {0x8001000,0xc809c8}, {0x400,0x845809d0}, {0x400,0x845809d8}, {0xc001400,0x801009e0}, {0x12001000,0x801809e8},
    {0x0,0x802009f0}, {0x6001400,0x802809f8}, {0x18001000,0x80300d00}, {0xc000000,0x80380d08}, {0x12001400,0x80400d10}, {0x1000,0x80480d18},
    {0x6000000,0x82500d20}, {0x18000800,0x80580d28}, {0xc001400,0x84580d30}, {0x12000c00,0x84580d38}, {0x1000,0x84580d40}, {0x6000400,0x84580d48},
    {0x18000000,0x84580d50}, {0xc000800,0x84580d58}, {0x0,0x82600d60}, {0x14001400,0x82680d68}, {0x1000,0x82700d70}, {0x4000000,0x82780d78},
    {0x8001400,0x82800d80}, {0x18001000,0x82880d88}, {0xc000000,0x82900d90}, {0x10001400,0x82980d98}, {0x1c001000,0x82a00da0}, {0x14000000,0x82a80da8},
    {0x1400,0x82b00db0}, {0x4001000,0x82d80db8}, {0x8000400,0x84580dc0}, {0x18000000,0x84580dc8}, {0xc000800,0x84580dd0}, {0x10001400,0x84580dd8},
    {0x1c000c00,0x82e00de0}, {0x14001000,0x82e80de8}, {0x0,0x82f00df0}, {0x4001400,0x82f80df8}, {0x8001000,0x2000900}, {0x18000000,0x2080908},
    {0xc001400,0x2100910}, {0x10001000,0x2180918}, {0x1c000000,0x2200920}, {0x14001400,0x2280928}, {0x1000,0x2300930}, {0x4000000,0x2580938},
    {0x8000800,0x84580940}, {0x18001400,0x84580948}, {0xc000c00,0x84580950}, {0x10001000,0x84580958}, {0x1c000400,0x2600960}, {0x14000000,0x2680968},
    {0x800,0x2700970}, {0x4001400,0x2780978}, {0x8000c00,0x2800980}, {0x18001000,0x2880988}, {0xc000400,0x2900990}, {0x10000000,0x2980998},
    {0x1c000800,0x2a009a0}, {0x14001400,0x2a809a8}, {0xc00,0x2b009b0}, {0x4001000,0x2b809b8}, {0x8000400,0x2c009c0}, {0x18000000,0x2c809c8},
    {0xc000800,0x2d009d0}, {0x10001400,0x2d809d8}, {0x1c000c00,0x2e009e0}, {0x14001000,0x2e809e8}, {0x400,0x2f009f0}, {0x4000000,0x2f809f8},
    {0x8000800,0x82000d00}, {0x18001400,0x82080d08}, {0xc000c00,0x82100d10}, {0x10001000,0x82180d18}, {0x1c000400,0x82200d20}, {0x14000000,0x82280d28},
    {0x800,0x82300d30}, {0x4001400,0x82380d38}, {0x8000c00,0x82400d40}, {0x18001000,0x82480d48}, {0xc000400,0x82500d50}, {0x10000000,0x82580d58},
    {0x1c000800,0x82600d60}, {0x14001400,0x82680d68}, {0xc00,0x82700d70}, {0x4001000,0x82780d78}, {0x8000400,0x82800d80}, {0x18000000,0x82880d88},
    {0xc000800,0x82900d90}, {0x10001400,0x82980d98}, {0x1c000c00,0x82a00da0}, {0x14001000,0x82a80da8}, {0x400,0x82b00db0}, {0x4000000,0x82b80db8},
    {0x8000800,0x82c00dc0}, {0x18001400,0x82c80dc8}, {0xc000c00,0x82d00dd0}, {0x10001000,0x82d80dd8}, {0x1c000400,0x82e00de0}, {0x14000000,0x82e80de8},
    {0x800,0x20005f0}, {0x4001400,0x845805f8}, {0x8000c00,0x84580100}, {0x18001000,0x2080108}, {0x400,0x84580110}, {0x0,0x84580118},
    {0x14000800,0x0}, {0x14000800,0x0}, {0x14000800,0x0},
  },
};
__constant__ uint2 c_act[2][135] = {
  {
    {0x81000458,0xa0000000}, {0x80004458,0xa0004008}, {0x80008458,0xa0008010}, {0x8000c458,0xa000c018}, {0x80010458,0xa0010020}, {0x14200,0xa0000028},
    {0x18208,0xa0004030}, {0x1c210,0xa0008038}, {0x3020218,0xa000c040}, {0x24228,0xa0000048}, {0x28238,0xa0008050}, {0x2c240,0xa000c058},
    {0x30248,0xa0000060}, {0x34250,0xa0008068}, {0x38258,0xa000c070}, {0x3c260,0xa0000078}, {0x328,0x4080}, {0x280,0x40004088},
    {0x5080358,0x80010090}, {0x88360,0x80000098}, {0x90368,0x800080a0}, {0x98370,0x800140a8}, {0xa0378,0x8000c0b0}, {0xa8290,0x800100b8},
    {0xb0298,0x800000c0}, {0xb82a0,0x800080c8}, {0x2a8,0x140d0}, {0x80000458,0x400140d8}, {0x70003a8,0xa00000e0}, {0x43b0,0xa00080e8},
    {0x83b8,0xa00140f0}, {0xc3c0,0xa000c0f8}, {0x103c8,0xa0010000}, {0x143d8,0xa0004008}, {0x182e0,0xa0000010}, {0x1c2e8,0xa0008018},
    {0x202f8,0xa000c020}, {0x80024208,0xa0004028}, {0x80028218,0xa0008030}, {0x8002c220,0xa000c038}, {0x80030228,0xa0004040}, {0x80034230,0xa0008048},
    {0x80038238,0xa000c050}, {0x8003c240,0xa0004058}, {0x80000458,0x20000060}, {0x80000330,0x80014068}, {0x80004338,0x8000c070}, {0x80008340,0x80010078},
    {0x8000c348,0x80004080}, {0x80010350,0x80000088}, {0x80014358,0x80008090}, {0x80018270,0x8000c098}, {0x8001c280,0x800040a0}, {0x80020290,0x800080a8},
    {0x80024298,0x8000c0b0}, {0x800282a0,0x800040b8}, {0x8002c2a8,0x800080c0}, {0x800302b0,0x8000c0c8}, {0x800342b8,0x800040d0}, {0x800382c0,0x800080d8},
    {0x8003c2c8,0x8000c0e0}, {0x800003b8,0x800100e8}, {0x800043c0,0x800040f0}, {0x800083c8,0x800000f8}, {0x8000c3d0,0x80008000}, {0x800103d8,0x80014008},
    {0x800143e0,0x8000c010}, {0x800182f0,0x80004018}, {0x1c200,0x80008020}, {0x20210,0x8000c028}, {0x24218,0x80004030}, {0x28220,0x80008038},
    {0x2c228,0x8000c040}, {0x30230,0x80004048}, {0x34238,0x80008050}, {0x38240,0x8000c058}, {0x3c248,0x80004060}, {0x918c338,0x60000068},
    {0x190340,0x60008070}, {0x194348,0x60014078}, {0x198350,0x6000c080}, {0x19c358,0x60010088}, {0x1a0360,0x60004090}, {0x1a4268,0x60000098},
    {0x1a8270,0x600080a0}, {0x1ac278,0x600140a8}, {0x1b0280,0x6000c0b0}, {0x1b4288,0x600100b8}, {0x1b8290,0x600040c0}, {0x1bc298,0x600000c8},
    {0x1c02a0,0x600080d0}, {0x1c42a8,0x600140d8}, {0x1c82b0,0x6000c0e0}, {0x1cc2b8,0x600100e8}, {0x1d02c0,0x600040f0}, {0x1d42c8,0x600000f8},
    {0x1d82d0,0x60008000}, {0x1dc2d8,0x60014008}, {0xb1e02e0,0x6000c010}, {0x1e42e8,0x60010018}, {0x1e82f0,0x60004020}, {0x1ec2f8,0x60000028},
    {0x801f0200,0x60008030}, {0x801f4208,0x60014038}, {0x801f8210,0x6000c040}, {0x801fc218,0x60010048}, {0x80200220,0x60004050}, {0x80204228,0x60000058},
    {0x80208230,0x60008060}, {0x8020c238,0x60014068}, {0x80210240,0x6000c070}, {0x80214248,0x60010078}, {0x80218250,0x60004080}, {0x8021c258,0x60000088},
    {0x8d220260,0x60008090}, {0x80224268,0x60014098}, {0x80228270,0x6000c0a0}, {0x8022c278,0x600100a8}, {0x80230280,0x600040b0}, {0x80234288,0x600000b8},
    {0x80238290,0x600080c0}, {0x8023c298,0x600140c8}, {0x802402a0,0x6000c0d0}, {0x802442a8,0x600100d8}, {0x802482b0,0x600040e0}, {0x8024c2b8,0x600000e8},
    {0x802502c0,0x600080f0}, {0x802542c8,0x600140f8}, {0x802582d0,0x6000c000}, {0x8025c2d8,0x60010008}, {0x801002e0,0x20004010}, {0x801042e8,0x20000018},
    {0x0,0x0}, {0x0,0x0}, {0x0,0x0},
  },
  {
    {0x91058458,0x40014100}, {0x5c220,0x40010108}, {0x60230,0x40004110}, {0x64300,0x40014118}, {0x68308,0x40010120}, {0x6c310,0x40004128},
    {0x70318,0x40014130}, {0x74320,0x40010138}, {0x78268,0x40008140}, {0x7c330,0x40014148}, {0x40270,0xa000c150}, {0x44338,0xa0010158},
    {0x48278,0xa0000160}, {0x4c340,0xa0008168}, {0x50348,0xa0014170}, {0x54350,0xa000c178}, {0x288,0x4180}, {0x380,0x40004188},
    {0x150c02b0,0x4000c190}, {0xc82b8,0x40010198}, {0xd0388,0x400041a0}, {0xd82c0,0x400001a8}, {0xe02c8,0x400081b0}, {0xe82d8,0x400141b8},
    {0xf0390,0x4000c1c0}, {0xf8398,0x400101c8}, {0x3a0,0x41d0}, {0x80000458,0x400041d8}, {0x170582f0,0x400141e0}, {0x8005c200,0x400101e8},
    {0x80060210,0x400001f0}, {0x643e0,0x400141f8}, {0x683e8,0x40010100}, {0x6c3f0,0x40000108}, {0x703f8,0x40014110}, {0x80074300,0x40010118},
    {0x80078308,0x40000120}, {0x8007c248,0x40008128}, {0x80040310,0xa0014130}, {0x80044250,0xa000c138}, {0x80048318,0xa0010140}, {0x8004c258,0xa0004148},
    {0x80050320,0xa0000150}, {0x80054328,0xa0008158}, {0x80000458,0x20000160}, {0x80040268,0x40014168}, {0x80044278,0x40010170}, {0x80048288,0x40000178},
    {0x8004c368,0x40014180}, {0x80050370,0x40010188}, {0x80054378,0x40000190}, {0x80058380,0x40014198}, {0x8005c388,0x400101a0}, {0x80060390,0x400001a8},
    {0x80064398,0x400141b0}, {0x800683a0,0x400101b8}, {0x8006c2d0,0x400041c0}, {0x800703a8,0x400001c8}, {0x800742d8,0x400081d0}, {0x800783b0,0x400141d8},
    {0x8007c2e0,0x4000c1e0}, {0x800402e8,0x400101e8}, {0x800442f8,0x400001f0}, {0x48208,0x400141f8}, {0x8004c3e8,0x40010100}, {0x800503f0,0x40000108},
    {0x800543f8,0x40014110}, {0x58300,0x40010118}, {0x5c308,0x40000120}, {0x60310,0x40014128}, {0x64318,0x40010130}, {0x68320,0x40000138},
    {0x6c250,0x40008140}, {0x70328,0x40014148}, {0x74258,0x4000c150}, {0x78330,0x40010158}, {0x7c260,0x40004160}, {0x918c338,0x20000168},
    {0x190340,0x20008170}, {0x194348,0x20014178}, {0x198350,0x2000c180}, {0x19c358,0x20010188}, {0x1a0360,0x20004190}, {0x1a4368,0x20000198},
    {0x1a8370,0x200081a0}, {0x1ac378,0x200141a8}, {0x1b0380,0x2000c1b0}, {0x1b4388,0x200101b8}, {0x1b8390,0x200041c0}, {0x1bc398,0x200001c8},
    {0x1c03a0,0x200081d0}, {0x1c43a8,0x200141d8}, {0x1c83b0,0x2000c1e0}, {0x1cc3b8,0x200101e8}, {0x1d03c0,0x200041f0}, {0x1d43c8,0x200001f8},
    {0x1d83d0,0x20008100}, {0x1dc3d8,0x20014108}, {0xb1e03e0,0x2000c110}, {0x1e43e8,0x20010118}, {0x1e83f0,0x20004120}, {0x1ec3f8,0x20000128},
    {0x801f0300,0x20008130}, {0x801f4308,0x20014138}, {0x801f8310,0x2000c140}, {0x801fc318,0x20010148}, {0x80200320,0x20004150}, {0x80204328,0x20000158},
    {0x80208330,0x20008160}, {0x8020c338,0x20014168}, {0x80210340,0x2000c170}, {0x80214348,0x20010178}, {0x80218350,0x20004180}, {0x8021c358,0x20000188},
    {0x8d220360,0x20008190}, {0x80224368,0x20014198}, {0x80228370,0x2000c1a0}, {0x8022c378,0x200101a8}, {0x80230380,0x200041b0}, {0x80234388,0x200001b8},
    {0x80238390,0x200081c0}, {0x8023c398,0x200141c8}, {0x802403a0,0x2000c1d0}, {0x802443a8,0x200101d8}, {0x802483b0,0x200041e0}, {0x8024c3b8,0x200001e8},
    {0x802503c0,0x200081f0}, {0x802543c8,0x200141f8}, {0x802583d0,0x2000c100}, {0x8025c3d8,0x20010108}, {0x801003e0,0x20004110}, {0x801043e8,0x20000118},
    {0x0,0x0}, {0x0,0x0}, {0x0,0x0},
  },
};
__constant__ uint2 c_w[1][138] = {
  {
    {0x84580000,0x20000}, {0x84580000,0x2026008}, {0x84580000,0x4038010}, {0x84580000,0x6032018}, {0x84580000,0x802c020}, {0x2000000,0xa000028},
    {0x2080000,0xc006030}, {0x2100000,0xe018038}, {0x2180000,0x10012040}, {0x2200000,0x1200c048}, {0x2280000,0x14000050}, {0x2300300,0x16006058},
    {0x2380308,0x18018060}, {0x2400310,0x1a012068}, {0x2480318,0x1c00c070}, {0x2500320,0x1e000078}, {0x2580328,0x6150}, {0x2600330,0x2018158},
    {0x2680338,0x4012160}, {0x2700340,0x600c168}, {0x2780348,0x8000170}, {0x3500000,0xa026178}, {0x3580000,0x18890}, {0x84580000,0x401c898},
    {0x3600000,0x80148a0}, {0x3680000,0xc00c8a8}, {0x84580000,0x100108b0}, {0x3700000,0x140008b8}, {0x3780000,0x180048c0}, {0x84580000,0x1c0288c8},
    {0x3980000,0x184e0}, {0x3b00000,0x200c4e8}, {0x84580000,0x40124f0}, {0x2c003c0,0x60004f8}, {0x2c803c8,0x8006400}, {0x2e00000,0xa018408},
    {0x2e80000,0xc00c410}, {0x2f00000,0xe012418}, {0x2f80000,0x10000420}, {0x82000000,0x12006428}, {0x82080000,0x14018430}, {0x821003e0,0x1600c438},
    {0x821803e8,0x18012440}, {0x822003f0,0x1a000448}, {0x822803f8,0x1c006450}, {0x82308300,0x1e018458}, {0x82388308,0xc530}, {0x82408310,0x2012538},
    {0x82488318,0x4000540}, {0x83200000,0x6006548}, {0x82588328,0x8018550}, {0x83300000,0xa02c558}, {0x83380000,0x14c68}, {0x83400000,0x2000c70},
    {0x83480000,0x4004c78}, {0x84580000,0x6008c80}, {0x83500000,0x8018c88}, {0x83580000,0xa00cc90}, {0x84580000,0xc010c98}, {0x83600000,0xe01cca0},
    {0x83680000,0x10014ca8}, {0x83700000,0x12000cb0}, {0x83780000,0x14004cb8}, {0x83800000,0x16008cc0}, {0x83880000,0x18018cc8}, {0x83900000,0x1a00ccd0},
    {0x83980000,0x1c010cd8}, {0x83a00000,0x1e03cce0}, {0x83a80000,0x150e8}, {0x83b00000,0x20010f0}, {0x83b80000,0x40050f8}, {0x83c00000,0x6009000},
    {0x83c80000,0x8019008}, {0x83d00000,0xa00d010}, {0x83d80000,0xc011018}, {0x83e00000,0xe01d020}, {0x83e80000,0x10015028}, {0x83f00000,0x12001030},
    {0x83f80000,0x14005038}, {0x3000000,0x16009040}, {0x3080000,0x18019048}, {0x3100000,0x1a00d050}, {0x3180000,0x1c011058}, {0x3200000,0x1e03d060},
    {0x3280000,0x6015468}, {0x3300000,0x8001470}, {0x3380000,0xa005478}, {0x3400000,0xc009480}, {0x3480000,0xe019488}, {0x3500000,0x1000d490},
    {0x3580000,0x12011498}, {0x3600000,0x1401d4a0}, {0x3680000,0x160154a8}, {0x3700000,0x180014b0}, {0x3780000,0x1a0054b8}, {0x3800000,0x1c0094c0},
    {0x3880000,0x1e0194c8}, {0x3900000,0x2000d4d0}, {0x3980000,0x220114d8}, {0x3a00000,0x2401d4e0}, {0x3a80000,0x260154e8}, {0x3b00000,0x280014f0},
    {0x3b80000,0x2a0054f8}, {0x3c00000,0x2c009400}, {0x3c80000,0x2e019408}, {0x3d00000,0x3000d410}, {0x3d80000,0x32011418}, {0x3e00000,0x3401d420},
    {0x3e80000,0x36015428}, {0x3f00000,0x38001430}, {0x3f80000,0x3a005438}, {0x83000000,0x3c009440}, {0x83080000,0x3e019448}, {0x83100000,0x4000d450},
    {0x83180000,0x42011458}, {0x83200000,0x4401d460}, {0x83280000,0x46015468}, {0x83300000,0x48001470}, {0x83380000,0x4a005478}, {0x83400000,0x4c009480},
    {0x83480000,0x4e019488}, {0x83500000,0x5000d490}, {0x83580000,0x52011498}, {0x83600000,0x5401d4a0}, {0x83680000,0x560154a8}, {0x83700000,0x580014b0},
    {0x83780000,0x5a0054b8}, {0x83800000,0x5c0094c0}, {0x83880000,0x5e0194c8}, {0x83900000,0x6000d4d0}, {0x83980000,0x620114d8}, {0x83a00000,0x6401d4e0},
    {0x83a80000,0x660154e8}, {0x83b00000,0x680014f0}, {0x83b80000,0x6a0054f8}, {0x83c00000,0x6c009400}, {0x83c80000,0x6e039408}, {0x0,0x0},
  },
};

constexpr int T_H = 0, T_O = 32, T_X1 = 64, T_ACT = 96, N_TILES = 208;
constexpr int G_H0 = 0, G_H1 = 1, G_O = 2, G_H2 = 3, G_ACT = 4, G_X1 = 7, G_HK = 15;

struct Scratch {
  uint4 img[8 * N_TILES * 1024];
  uint32_t mod0[4 * 4 * 512];
  uint32_t modp[4096];
  uint2 stat[32 * 8 * 64];
  uint4 halo[16 * 16 * 128];
  uint32_t cnt[8 * 32];
  uint32_t ep[(NCTA + 4) * 32];
};
__device__ __align__(1024) Scratch g_s;

struct Ptrs {
  const __nv_bfloat16 *x, *c;
  Scratch* s;
  __nv_bfloat16* out;
};
struct Params {
  CUtensorMap mWqkv, mWo, mWg, mWu, mWd, mOut, mWm2, mX;
};

__device__ __forceinline__ uint32_t smem_u32(const void* p) { return (uint32_t)__cvta_generic_to_shared(p); }
__device__ __forceinline__ void mbar_init(uint32_t bar, uint32_t cnt) { asm volatile("mbarrier.init.shared::cta.b64 [%0], %1;" ::"r"(bar), "r"(cnt)); }
__device__ __forceinline__ void mbar_expect_tx(uint32_t bar, uint32_t bytes) { asm volatile("mbarrier.arrive.expect_tx.shared::cta.b64 _, [%0], %1;" ::"r"(bar), "r"(bytes) : "memory"); }
__device__ __forceinline__ void mbar_arrive(uint32_t bar) { asm volatile("mbarrier.arrive.shared::cta.b64 _, [%0];" ::"r"(bar) : "memory"); }
__device__ __forceinline__ void mbar_arrive_remote(uint32_t bar_cluster) { asm volatile("mbarrier.arrive.shared::cluster.b64 _, [%0];" ::"r"(bar_cluster) : "memory"); }
__device__ __forceinline__ uint32_t mapa(uint32_t a, uint32_t cta) { uint32_t r; asm volatile("mapa.shared::cluster.u32 %0, %1, %2;" : "=r"(r) : "r"(a), "r"(cta)); return r; }
__device__ __forceinline__ void mbar_wait(uint32_t bar, uint32_t parity) {
  asm volatile("{\n.reg .pred p;\nW: mbarrier.try_wait.parity.shared::cta.b64 p, [%0], %1;\n@!p bra W;\n}" ::"r"(bar), "r"(parity) : "memory");
}
__device__ __forceinline__ void mbar_wait_bounded(uint32_t bar, uint32_t parity) {
  asm volatile("{\n.reg .pred p;\n.reg .u32 c;\nmov.u32 c, 0;\n"
               "W: mbarrier.try_wait.parity.shared::cta.b64 p, [%0], %1;\n@p bra D;\n"
               "add.u32 c, c, 1;\nsetp.lt.u32 p, c, 0x200000;\n@p bra W;\ntrap;\nD:\n}" ::"r"(bar), "r"(parity) : "memory");
}
constexpr uint32_t POLL_MAX = 1u << 20;
__device__ __forceinline__ void guard(uint32_t it) { asm volatile("{\n.reg .pred p;\nsetp.gt.u32 p, %0, 0x100000;\n@p trap;\n}" ::"r"(it)); }
__device__ __forceinline__ bool mbar_test(uint32_t bar, uint32_t parity) {
  uint32_t p; asm volatile("{\n.reg .pred P;\nmbarrier.test_wait.parity.shared::cta.b64 P, [%1], %2;\nselp.u32 %0, 1, 0, P;\n}" : "=r"(p) : "r"(bar), "r"(parity) : "memory"); return p;
}
__device__ __forceinline__ bool elect_one() {
  uint32_t p; asm volatile("{\n.reg .pred P;\nelect.sync _|P, 0xffffffff;\nselp.u32 %0, 1, 0, P;\n}" : "=r"(p)); return p;
}
__device__ __forceinline__ bool only_one() { asm volatile("{\n.reg .pred P;\nelect.sync _|P, 0xffffffff;\n@!P exit;\n}" ::: "memory"); return true; }
__device__ __forceinline__ void tma2d(uint32_t dst, const CUtensorMap* m, uint32_t bar, int c0, int c1) {
  asm volatile("cp.async.bulk.tensor.2d.shared::cluster.global.mbarrier::complete_tx::bytes [%0], [%1, {%3, %4}], [%2];" ::"r"(dst), "l"(m), "r"(bar), "r"(c0), "r"(c1) : "memory");
}
__device__ __forceinline__ uint64_t evict_first() { uint64_t p; asm("createpolicy.fractional.L2::evict_first.b64 %0, 1.0;" : "=l"(p)); return p; }
__device__ __forceinline__ void tma2d_once(uint32_t dst, const CUtensorMap* m, uint32_t bar, int c0, int c1) {
  asm volatile("cp.async.bulk.tensor.2d.shared::cluster.global.mbarrier::complete_tx::bytes.L2::cache_hint [%0], [%1, {%3, %4}], [%2], %5;" ::"r"(dst), "l"(m), "r"(bar), "r"(c0), "r"(c1), "l"(evict_first()) : "memory");
}
__device__ __forceinline__ void tma5d_once(uint32_t dst, const CUtensorMap* m, uint32_t bar, int c0, int c4) {
  asm volatile("cp.async.bulk.tensor.5d.shared::cluster.global.mbarrier::complete_tx::bytes.L2::cache_hint [%0], [%1, {%3, %5, %5, %5, %4}], [%2], %6;" ::"r"(dst), "l"(m), "r"(bar), "r"(c0), "r"(c4), "r"(0), "l"(evict_first()) : "memory");
}
__device__ __forceinline__ void tma5d(uint32_t dst, const CUtensorMap* m, uint32_t bar, int c0, int c4) {
  asm volatile("cp.async.bulk.tensor.5d.shared::cluster.global.mbarrier::complete_tx::bytes [%0], [%1, {%3, %5, %5, %5, %4}], [%2];" ::"r"(dst), "l"(m), "r"(bar), "r"(c0), "r"(c4), "r"(0) : "memory");
}
__device__ __forceinline__ void tma2d_st(const CUtensorMap* m, uint32_t src, int c0, int c1) {
  asm volatile("cp.async.bulk.tensor.2d.global.shared::cta.bulk_group [%0, {%2, %3}], [%1];" ::"l"(m), "r"(src), "r"(c0), "r"(c1) : "memory");
}
__device__ __forceinline__ void bulk_g2s(uint32_t dst, const void* src, uint32_t bytes, uint32_t bar) {
  asm volatile("cp.async.bulk.shared::cluster.global.mbarrier::complete_tx::bytes [%0], [%1], %2, [%3];" ::"r"(dst), "l"(src), "r"(bytes), "r"(bar) : "memory");
}
__device__ __forceinline__ void bulk_g2s_mc(uint32_t dst, const void* src, uint32_t bytes, uint32_t bar) {
  asm volatile("cp.async.bulk.shared::cluster.global.mbarrier::complete_tx::bytes.multicast::cluster [%0], [%1], %2, [%3], %4;" ::"r"(dst), "l"(src), "r"(bytes), "r"(bar), "h"((uint16_t)3) : "memory");
}
__device__ __forceinline__ void st_async(uint32_t dst, uint32_t bar, uint32_t a, uint32_t b, uint32_t c, uint32_t d) {
  asm volatile("st.async.weak.shared::cluster.mbarrier::complete_tx::bytes.v4.b32 [%0], {%2,%3,%4,%5}, [%1];" ::"r"(dst), "r"(bar), "r"(a), "r"(b), "r"(c), "r"(d) : "memory");
}
__device__ __forceinline__ void bulk_commit() { asm volatile("cp.async.bulk.commit_group;" ::: "memory"); }
__device__ __forceinline__ void bulk_wait_read() { asm volatile("cp.async.bulk.wait_group.read 0;" ::: "memory"); }
__device__ __forceinline__ void fence_async_smem() { asm volatile("fence.proxy.async.shared::cta;" ::: "memory"); }
__device__ __forceinline__ void fence_async_glob() { asm volatile("fence.proxy.async.global;" ::: "memory"); }
__device__ __forceinline__ void prefetch_tmap(const CUtensorMap* m) { asm volatile("prefetch.tensormap [%0];" ::"l"(m) : "memory"); }
__device__ __forceinline__ void wg_fence() { asm volatile("wgmma.fence.sync.aligned;" ::: "memory"); }
__device__ __forceinline__ void wg_commit() { asm volatile("wgmma.commit_group.sync.aligned;" ::: "memory"); }
template <int N> __device__ __forceinline__ void wg_wait() { asm volatile("wgmma.wait_group.sync.aligned %0;" ::"n"(N) : "memory"); }
template <int N> __device__ __forceinline__ void fence_regs(float (&a)[N]) {
#pragma unroll
  for (int i = 0; i < N; i++) asm volatile("" : "+f"(a[i])::"memory");
}
__device__ __forceinline__ uint32_t make_desc(uint32_t addr, uint32_t lbo) { return ((addr & 0x3FFFF) >> 4) | ((lbo >> 4) << 16); }
__device__ __forceinline__ void named_sync(int id, int n) { asm volatile("bar.sync %0, %1;" ::"r"(id), "r"(n) : "memory"); }
__device__ __forceinline__ uint32_t ld_relaxed(const void* p) { uint32_t v; asm volatile("ld.relaxed.gpu.global.u32 %0, [%1];" : "=r"(v) : "l"(p) : "memory"); return v; }
__device__ __forceinline__ uint32_t ld_relaxed_line(const void* p) { uint32_t v; asm volatile("ld.relaxed.gpu.global.L2::128B.u32 %0, [%1];" : "=r"(v) : "l"(p) : "memory"); return v; }
__device__ __forceinline__ void red_relaxed(uint32_t* p, uint32_t v) { asm volatile("red.relaxed.gpu.global.add.u32 [%0], %1;" ::"l"(p), "r"(v) : "memory"); }
__device__ __forceinline__ void st_relaxed(uint32_t* p, uint32_t v) { asm volatile("st.relaxed.gpu.global.u32 [%0], %1;" ::"l"(p), "r"(v) : "memory"); }
__device__ __forceinline__ uint2 ld_relaxed_b64(const uint2* p) {
  uint64_t a; asm volatile("ld.relaxed.gpu.global.b64 %0, [%1];" : "=l"(a) : "l"(p) : "memory");
  return make_uint2((uint32_t)a, (uint32_t)(a >> 32));
}
__device__ __forceinline__ void st_relaxed_b64(void* p, uint32_t lo, uint32_t hi) {
  uint64_t v = ((uint64_t)hi << 32) | lo;
  asm volatile("st.relaxed.gpu.global.b64 [%0], %1;" ::"l"(p), "l"(v) : "memory");
}
__device__ __forceinline__ void st_relaxed_v4(uint4* p, uint32_t a, uint32_t b, uint32_t c, uint32_t d) {
  asm volatile("st.relaxed.gpu.global.v4.u32 [%0], {%1,%2,%3,%4};" ::"l"(p), "r"(a), "r"(b), "r"(c), "r"(d) : "memory");
}
__device__ __forceinline__ bool empty(const uint4& v) { return v.x == ~0u || v.y == ~0u || v.z == ~0u || v.w == ~0u; }
__device__ __forceinline__ uint32_t tag_of(uint32_t ep) { return ep % 3 + 1; }
__device__ __forceinline__ uint32_t tagf(float v, uint32_t ep) {
  uint32_t r; asm volatile("lop3.b32 %0, %1, %2, 3, 0xD8;" : "=r"(r) : "r"(__float_as_uint(v)), "r"(ep)); return r;
}
__device__ __forceinline__ uint32_t tag_bad(const uint4& v, uint32_t ep) { return ((v.x ^ ep) | (v.y ^ ep) | (v.z ^ ep) | (v.w ^ ep)) & 3u; }
__device__ __forceinline__ uint4 ld_relaxed_v4(const void* p) {
  uint4 v; asm volatile("ld.relaxed.gpu.global.v4.u32 {%0,%1,%2,%3}, [%4];" : "=r"(v.x), "=r"(v.y), "=r"(v.z), "=r"(v.w) : "l"(p) : "memory"); return v;
}
__device__ __forceinline__ uint32_t ldg32(const void* p) { uint32_t v; asm volatile("ld.global.u32 %0, [%1];" : "=r"(v) : "l"(p) : "memory"); return v; }
__device__ __forceinline__ void stg128(uint4* p, uint32_t a, uint32_t b, uint32_t c, uint32_t d) {
  asm volatile("st.global.v4.b32 [%0], {%1,%2,%3,%4};" ::"l"(p), "r"(a), "r"(b), "r"(c), "r"(d) : "memory");
}
__device__ __forceinline__ void landed(uint32_t v) { if (__all_sync(~0u, v == 0xffffffffu)) __nanosleep(1); }
__device__ __forceinline__ void publish(uint32_t seen, uint32_t* cnt, uint32_t inc) {
  landed(seen);
  if (elect_one()) red_relaxed(cnt, inc);
}
__device__ __forceinline__ uint32_t pack_bf16(float lo, float hi) { uint32_t r; asm("cvt.rn.bf16x2.f32 %0, %1, %2;" : "=r"(r) : "f"(hi), "f"(lo)); return r; }
__device__ __forceinline__ float bf_lo(uint32_t v) { return __uint_as_float(v << 16); }
__device__ __forceinline__ float bf_hi(uint32_t v) { return __uint_as_float(v & 0xffff0000u); }
__device__ __forceinline__ uint32_t hmul2_bf16(uint32_t a, uint32_t b) { uint32_t r; asm("mul.rn.bf16x2 %0, %1, %2;" : "=r"(r) : "r"(a), "r"(b)); return r; }
__device__ __forceinline__ uint32_t hadd2_bf16(uint32_t a, uint32_t b) { uint32_t r; asm("add.rn.bf16x2 %0, %1, %2;" : "=r"(r) : "r"(a), "r"(b)); return r; }
__device__ __forceinline__ uint32_t hfma2_bf16(uint32_t a, uint32_t b, uint32_t c) { uint32_t r; asm("fma.rn.bf16x2 %0, %1, %2, %3;" : "=r"(r) : "r"(a), "r"(b), "r"(c)); return r; }
__device__ __forceinline__ void wgmma_n8(float (&d)[4], uint32_t descA, uint32_t descB, int scaleD) {
  asm volatile("{\n.reg .pred p;\n.reg .b64 da, db;\nmov.b64 da, {%4, 0x40000040};\nmov.b64 db, {%5, 0x40000040};\nsetp.ne.b32 p, %6, 0;\n"
               "wgmma.mma_async.sync.aligned.m64n8k16.f32.bf16.bf16 {%0,%1,%2,%3}, da, db, p, 1, 1, 1, 0;\n}\n"
               : "+f"(d[0]), "+f"(d[1]), "+f"(d[2]), "+f"(d[3]) : "r"(descA), "r"(descB), "r"(scaleD));
}
__device__ __forceinline__ float ex2(float x) { float r; asm("ex2.approx.ftz.f32 %0, %1;" : "=f"(r) : "f"(x)); return r; }
__device__ __forceinline__ float rcp(float x) { float r; asm("rcp.approx.ftz.f32 %0, %1;" : "=f"(r) : "f"(x)); return r; }
__device__ __forceinline__ float silu_f(float x) { return x * rcp(1.f + ex2(x * -1.4426950408889634f)); }
__device__ __forceinline__ float swiglu(float h, float hu) {
  float t; asm("tanh.approx.f32 %0, %1;" : "=f"(t) : "f"(h));
  return fmaf(hu, t, hu);
}
__device__ __forceinline__ void ldsm4(uint32_t addr, uint32_t& a, uint32_t& b, uint32_t& c, uint32_t& d) {
  asm volatile("ldmatrix.sync.aligned.m8n8.x4.shared.b16 {%0,%1,%2,%3}, [%4];" : "=r"(a), "=r"(b), "=r"(c), "=r"(d) : "r"(addr) : "memory");
}
__device__ __forceinline__ void stsm4(uint32_t addr, uint32_t a, uint32_t b, uint32_t c, uint32_t d) {
  asm volatile("stmatrix.sync.aligned.m8n8.x4.shared.b16 [%0], {%1,%2,%3,%4};" ::"r"(addr), "r"(a), "r"(b), "r"(c), "r"(d) : "memory");
}
__device__ __forceinline__ void sts128(uint32_t addr, uint32_t a, uint32_t b, uint32_t c, uint32_t d) {
  asm volatile("st.shared.v4.b32 [%0], {%1,%2,%3,%4};" ::"r"(addr), "r"(a), "r"(b), "r"(c), "r"(d) : "memory");
}
__device__ __forceinline__ void sts64(uint32_t addr, uint32_t a, uint32_t b) { asm volatile("st.shared.v2.b32 [%0], {%1,%2};" ::"r"(addr), "r"(a), "r"(b) : "memory"); }
__device__ __forceinline__ void sts32(uint32_t addr, uint32_t a) { asm volatile("st.shared.b32 [%0], %1;" ::"r"(addr), "r"(a) : "memory"); }
__device__ __forceinline__ uint4 lds128(uint32_t addr) {
  uint4 v; asm volatile("ld.shared.v4.b32 {%0,%1,%2,%3}, [%4];" : "=r"(v.x), "=r"(v.y), "=r"(v.z), "=r"(v.w) : "r"(addr) : "memory"); return v;
}
__device__ __forceinline__ uint32_t lds32(uint32_t addr) { uint32_t v; asm volatile("ld.shared.b32 %0, [%1];" : "=r"(v) : "r"(addr) : "memory"); return v; }
__device__ __forceinline__ uint32_t movm(uint32_t a) { uint32_t d; asm volatile("movmatrix.sync.aligned.m8n8.trans.b16 %0, %1;" : "=r"(d) : "r"(a)); return d; }
__device__ __forceinline__ void mma16816(float (&c)[4], uint32_t a0, uint32_t a1, uint32_t a2, uint32_t a3, uint32_t b0, uint32_t b1) {
  asm volatile("mma.sync.aligned.m16n8k16.row.col.f32.bf16.bf16.f32 {%0,%1,%2,%3},{%4,%5,%6,%7},{%8,%9},{%0,%1,%2,%3};"
               : "+f"(c[0]), "+f"(c[1]), "+f"(c[2]), "+f"(c[3]) : "r"(a0), "r"(a1), "r"(a2), "r"(a3), "r"(b0), "r"(b1));
}
__device__ __forceinline__ void mma16816z(float (&c)[4], uint32_t a0, uint32_t a1, uint32_t a2, uint32_t a3, uint32_t b0, uint32_t b1) {
  asm volatile("mma.sync.aligned.m16n8k16.row.col.f32.bf16.bf16.f32 {%0,%1,%2,%3},{%4,%5,%6,%7},{%8,%9},{%10,%10,%10,%10};"
               : "=f"(c[0]), "=f"(c[1]), "=f"(c[2]), "=f"(c[3]) : "r"(a0), "r"(a1), "r"(a2), "r"(a3), "r"(b0), "r"(b1), "f"(0.f));
}
__device__ __forceinline__ void mma1688(float (&c)[4], uint32_t a0, uint32_t a1, uint32_t b0) {
  asm volatile("mma.sync.aligned.m16n8k8.row.col.f32.bf16.bf16.f32 {%0,%1,%2,%3},{%4,%5},{%6},{%0,%1,%2,%3};"
               : "+f"(c[0]), "+f"(c[1]), "+f"(c[2]), "+f"(c[3]) : "r"(a0), "r"(a1), "r"(b0));
}
__device__ __forceinline__ float quad_max(float v) { v = fmaxf(v, __shfl_xor_sync(~0u, v, 1)); return fmaxf(v, __shfl_xor_sync(~0u, v, 2)); }
__device__ __forceinline__ float quad_sum(float v) { v += __shfl_xor_sync(~0u, v, 1); return v + __shfl_xor_sync(~0u, v, 2); }
__device__ __forceinline__ uint32_t opaque(uint32_t v) { asm volatile("" : "+r"(v)); return v; }
__device__ __forceinline__ uint32_t tid_now() { uint32_t v; asm volatile("mov.u32 %0, %%tid.x;" : "=r"(v)); return v; }
__device__ __forceinline__ void arrive_after(uint32_t bar, float v) {
  asm volatile("{\n.reg .pred p, q;\n.reg .b32 c;\nmov.b32 c, %1;\nelect.sync _|q, 0xffffffff;\n"
               "L: @q mbarrier.arrive.shared::cta.b64 _, [%0];\nsetp.eq.u32 p, c, 0x7fedcba9;\nadd.u32 c, c, 1;\nsetp.ne.u32 q, c, c;\n@p bra L;\n}"
               ::"r"(bar), "r"(__float_as_uint(v)) : "memory");
}
__device__ __forceinline__ int since(int t0) { return (int)((uint32_t)clock() - (uint32_t)t0); }
__device__ __forceinline__ void until(int t0, uint32_t t) { while ((uint32_t)since(t0) < t) {} }
__device__ __forceinline__ void in_order() { const int t = (int)clock(); while (since(t) < 0) {} }
__device__ __forceinline__ void spin(int clocks) { until((int)clock(), clocks); }

constexpr float ATT_SCALE_LOG2E = 0.17677669529663687f * 1.4426950408889634f;

constexpr int T_XA = 2600;
constexpr int P_XB = 100;
constexpr int P_ACT = 140;
constexpr int T_Q2 = 3750;
constexpr int T_Q3 = 4150;
constexpr int T_XB = 8050;
constexpr int DELAY_ST = 150;
constexpr int T_W0 = 3200;
constexpr int T_G0 = 4500;
constexpr int T_G1 = 7250;
constexpr int P_G2 = 690;
constexpr int P_G2B = 820;
constexpr int F_G2A = 700;
constexpr int F_G2B = 750;
constexpr int P_Q = 240;
constexpr int T_W = 5500;
constexpr int P_W = 1200;
constexpr int DELAY_HELP = 3000;

struct Pipe {
  const uint2* tab;
  uint32_t bars, peer_bars;
  uint2 nx;
  uint32_t prev;
  bool ready;
  bool lead;
  __device__ __forceinline__ uint2 begin(int n) {
    const uint2 e = nx;
    nx = tab[n + 1];
    if (!ready) {
      mbar_wait(bars + (e.y & 0x3ff), (e.y >> 10) & 1);
      mbar_wait(bars + ((e.y >> 16) & 0x7ff), e.y >> 31);
    }
    ready = false;
    return e;
  }
  __device__ __forceinline__ void release_now(uint32_t y) {
    asm volatile("{\n.reg .pred p, q;\n.reg .b32 c;\nmov.b32 c, %2;\nelect.sync _|q, 0xffffffff;\nsetp.ne.and.u32 q, c, 0, q;\n"
                 "L: @q mbarrier.arrive.shared::cta.b64 _, [%0];\n@q mbarrier.arrive.shared::cluster.b64 _, [%1];\n"
                 "setp.eq.u32 p, c, 1;\nadd.u32 c, c, 1;\n@p bra L;\n}"
                 ::"r"(bars + 512 + (y & 0x3ff)), "r"(peer_bars + 512 + (y & 0x3ff)), "r"(opaque(lead ? y & 0x800 : 0)) : "memory");
  }
  template <bool PAUSES = false> __device__ __forceinline__ void end(uint32_t y) {
    const bool r0 = mbar_test(bars + (nx.y & 0x3ff), (nx.y >> 10) & 1), r1 = mbar_test(bars + ((nx.y >> 16) & 0x7ff), nx.y >> 31);
    wg_wait<1>();
    release(prev);
    prev = y;
    if (PAUSES && (y & 0x1000)) { wg_wait<0>(); release(y); prev = 0; }
    ready = __all_sync(~0u, r0 && r1);
  }
  __device__ __forceinline__ void release(uint32_t y) {
    if (lead && (y & 0x800)) { if (elect_one()) { mbar_arrive(bars + 512 + (y & 0x3ff)); mbar_arrive_remote(peer_bars + 512 + (y & 0x3ff)); } }
  }
};
__device__ __forceinline__ constexpr uint32_t qa(int q) { return (q >> 1) * 256 + (q & 1) * 2; }

__device__ __forceinline__ uint32_t img_pos(uint32_t w, uint32_t lane) { return (w * 16 + (lane >> 2)) * 4 + ((lane & 3) ^ (lane >> 3)); }
__device__ __forceinline__ uint32_t img_line(uint32_t w, uint32_t lane) { return (lane >> 3) * 256 + w * 64 + (lane & 7) * 8; }

template <int MULTICAST>
__device__ __forceinline__ void tiles(uint32_t bars, const uint2* tab, uint2& nx, int n0, int n1, uint32_t dst, const char* src, uint32_t bytes,
                                      const uint32_t* cnt, uint32_t target, int pace, int head) {
  int due = 0;
#pragma unroll 1
  for (int n = n0; n < n1; n++) {
    const uint2 e = nx;
    nx = tab[n + 1];
    const uint32_t fb = bars + (e.y & 0x3ff);
    mbar_expect_tx(fb, (e.y >> 29) << 13);
    if (e.x & 0x1000000) {
      while ((int32_t)(ld_relaxed_line(cnt + ((e.x >> 25) & 31)) - target) < 0) {}
      asm volatile("fence.acquire.gpu;" ::: "memory"); fence_async_glob();
      if (!MULTICAST) due = since(head);
    }
    mbar_wait(bars + (e.x & 0x7ff), e.x >> 31);
    if (MULTICAST) bulk_g2s_mc(dst + (e.y & 0x3c000), src + (e.x & 0x3fc000), bytes, fb);
    else {
      until(due, (n - n0) * pace);
      bulk_g2s(dst + (e.y & 0x3c000), src + (e.x & 0x3fc000), bytes, fb);
    }
  }
}

template <int BOXES>
__device__ __forceinline__ void weights(uint32_t sb, uint2& nx, int& n, const CUtensorMap* m0, const CUtensorMap* m1, const CUtensorMap* m2, int c0, int c1, int c2, int dk) {
  const uint32_t bars = sb + BAR_OFF;
#pragma unroll 1
  for (bool more = true; more; n++) {
    const uint2 e = nx;
    nx = c_w[0][n + 1];
    more = !(e.y & 0x20000);
    const uint32_t fb = bars + (e.y & 0x3ff), dst = sb + W_OFF + (e.y & 0x1e000);
    const int k0 = (e.y >> 24) + dk;
    if (e.x & 0x7ff) mbar_wait(bars + (e.x & 0x7ff), (e.x >> 15) & 1);
    mbar_wait(bars + ((e.x >> 16) & 0x7ff), e.x >> 31);
    if (BOXES == 2) { tma5d_once(dst, m0, fb, c0, k0); tma5d_once(dst + 8192, m1, fb, c1, k0); }
    else { tma5d(dst, m0, fb, c0, k0); tma5d(dst + 8192, m1, fb, c1, k0); tma5d(dst + 16384, m2, fb, c2, k0); }
  }
}

__device__ __forceinline__ void mod_slice(uint32_t sb, uint32_t* dst, uint32_t tag, uint32_t w, uint32_t lane) {
  float e[4];
#pragma unroll 1
  for (int kb = 0; kb < 4; kb++) {
    mbar_wait(sb + BAR_OFF + B_SL + 8 * kb, 0);
    wg_fence();
#pragma unroll
    for (int q = 0; q < 4; q++) wgmma_n8(e, make_desc(SMEM_BASE + SL_OFF + kb * 8192, 8192) + q * 128, make_desc(SMEM_BASE + TAB_OFF + 4096 + kb * 256, 16) + q * 2, kb | q);
    wg_commit();
  }
  wg_wait<0>();
  fence_regs(e);
  if ((lane & 3) == 0) { st_relaxed(dst + w * 16 + (lane >> 2), tagf(e[0], tag)); st_relaxed(dst + w * 16 + 8 + (lane >> 2), tagf(e[2], tag)); }
  if (w == 0 && lane == 0) mbar_arrive(sb + BAR_OFF + B_SLE);
  __syncwarp();
}

__device__ __forceinline__ int mod_group(int job, int hc) { return (job >> 1) * 16 + hc * 4 + (job & 1) * 2; }

template <bool BY_SM>
__global__ void __cluster_dims__(2, 1, 1) __launch_bounds__(NTHREADS, 1) fused_kernel(const Ptrs Q, const __grid_constant__ Params P) {
  extern __shared__ __align__(1024) uint8_t smem_raw[];
  const int t0 = (int)clock();
  int cta = blockIdx.x;
  {
    uint32_t smid;
    asm volatile("mov.u32 %0, %%smid;" : "=r"(smid));
    const int tp = smid >> 1;
    const int cl = tp < 32 ? tp : (tp < 60 ? tp + 1 + (tp - 32) / 7 : (tp < 62 ? tp + 4 : (tp - 58) * 8));
    if (BY_SM) cta = cl * 2 + (cta & 1);
    cta = __shfl_sync(~0u, cta, 0);
  }
  const int grp = cta >> 4, j = cta & 15, rank = cta & 1, typ = j >> 3;
  const int wg = __shfl_sync(~0u, (int)threadIdx.x >> 7, 0);
  const int warp = __shfl_sync(~0u, (int)threadIdx.x >> 5, 0);
  const uint32_t sb = mapa(SMEM_BASE, rank), bars = sb + BAR_OFF;
  if (warp == 10 && cta < NCTA && elect_one()) {
    prefetch_tmap(&P.mWm2);
#pragma unroll
    for (int i = 0; i < 4; i++) mbar_init(bars + B_SL + 8 * i, 1);
    fence_async_smem();
    if (cta < 64) {
#pragma unroll
      for (int i = 0; i < 4; i++) {
        mbar_expect_tx(bars + B_SL + 8 * i, 8192);
        tma2d_once(sb + SL_OFF + i * 8192, &P.mWm2, bars + B_SL + 8 * i, ((cta >> 4) & 1) * D_ + (cta >> 5) * 256 + ((cta >> 2) & 3) * 64, (cta & 3) * 256 + i * 64);
      }
    }
  }
  __syncwarp();

  if (cta >= NCTA) {
    const uint32_t lane = tid_now() & 31, cf = sb + 196608, hb = cf + 16384;
    const int hc = cta - NCTA;
    if (threadIdx.x == 0) {
#pragma unroll 1
      for (int i = 0; i < 48; i++) mbar_init(hb + 8 * i, 1);
#pragma unroll 1
      for (int i = 0; i < 24; i++) mbar_init(bars + 8 * i, (i >> 1) == 6 ? 4 : 1);
    }
    const uint32_t ep = ld_relaxed(&Q.s->ep[cta * 32 + lane]) + 1;
#pragma unroll 1
    for (int kb = warp; kb < 16; kb += 12) {
      const uint32_t cv = ((const uint32_t*)Q.c)[kb * 32 + lane];
      sts32(cf + kb * 256 + (lane & 3) * 4 + (((lane >> 2) ^ ((2 * kb) & 7)) << 4), pack_bf16(silu_f(bf_lo(cv)), silu_f(bf_hi(cv))));
    }
    fence_async_smem();
    __syncthreads();
    if (wg == 2) {
      if (elect_one()) {
        spin(DELAY_HELP);
        uint32_t s = warp & 3, ph = 1;
#pragma unroll 1
        for (int n = (warp >> 1) & 1; n < 8 * 16; n += 2) {
          mbar_wait(hb + 8 * (24 + s), ph);
          mbar_expect_tx(hb + 8 * s, 8192);
          tma2d_once(sb + s * 8192, &P.mWm2, hb + 8 * s, (32 + mod_group(n >> 4, hc) + (warp & 1)) * 64, (n & 15) * 64);
          s += 4; if (s >= 24) { s -= 24; ph ^= 1; }
        }
      }
      __syncwarp();
      if (warp == 8) Q.s->ep[cta * 32 + lane] = ep;
    } else {
      uint32_t s = wg, ph = 0;
#pragma unroll 1
      for (int job = 0; job < 8; job++) {
        float e[4];
#pragma unroll 1
        for (int kb = 0; kb < 16; kb += 4) {
#pragma unroll 1
          for (int i = 0; i < 4; i++) {
            mbar_wait(hb + 8 * (s + 2 * i), ph);
            wg_fence();
#pragma unroll
            for (int q = 0; q < 4; q++)
              wgmma_n8(e, make_desc(SMEM_BASE, 8192) + (s + 2 * i) * 512 + q * 128, make_desc(SMEM_BASE + 196608, 16) + (kb + i) * 16 + q * 2, kb | i | q);
            wg_commit();
          }
          wg_wait<0>();
          if ((warp & 3) == 0 && elect_one()) {
#pragma unroll
            for (int i = 0; i < 4; i++) mbar_arrive(hb + 8 * (24 + s + 2 * i));
          }
          s += 8; if (s >= 24) { s -= 24; ph ^= 1; }
        }
        fence_regs(e);
        if ((lane & 3) == 0) {
          uint32_t* dst = Q.s->modp + (mod_group(job, hc) + wg) * 64 + (warp & 3) * 16 + (lane >> 2);
          st_relaxed(dst, tagf(e[0], tag_of(ep))); st_relaxed(dst + 8, tagf(e[2], tag_of(ep)));
          const uint32_t g = pack_bf16(2.f * __uint_as_float(tagf(e[0], tag_of(ep))), 2.f * __uint_as_float(tagf(e[2], tag_of(ep))));
          const uint32_t a = sb + PAR_OFF + ((job & 1) * 4 + wg * 2 + ((warp >> 1) & 1)) * 64 + (lane >> 3) * 16 + (warp & 1) * 8 + ((lane >> 2) & 1) * 2;
          asm volatile("st.shared.u16 [%0], %1;\nst.shared.u16 [%0 + 4], %2;" ::"r"(a), "h"((uint16_t)g), "h"((uint16_t)(g >> 16)) : "memory");
        }
        __syncwarp();
      }
    }
    __syncthreads();
    if (warp == 8) {
      if (only_one()) {
        mbar_expect_tx(bars + 64, N_HK * 32768);
#pragma unroll 1
        for (int i = 0; i < 4 * N_HK; i++) tma5d(sb + i * 8192, &P.mWd, bars + 64, hc * 256 + (i & 3) * 64, (i >> 2) * 2);
        uint32_t n = 0;
#pragma unroll 1
        for (int rb = 0; rb < 16; rb++) {
          while ((int32_t)(ld_relaxed(Q.s->cnt + (rb & 7) * 32 + (rb < 8 ? G_HK : 8 + G_ACT)) - (rb < 8 ? 4 * N_HK : 64) * ep) < 0) __nanosleep(50);
          asm volatile("fence.acquire.gpu;" ::: "memory"); fence_async_glob();
#pragma unroll 1
          for (int i = 0; i < 2 * N_HK; i++, n++) {
            mbar_wait(bars + 128 + 8 * (n & 7), ((n >> 3) & 1) ^ 1);
            mbar_expect_tx(bars + 8 * (n & 7), 8192);
            bulk_g2s(sb + 98304 + (n & 7) * 8192, Q.s->img + (size_t)((rb & 7) * N_TILES + T_ACT + (rb >> 3) * 56 + i % N_HK) * 1024 + i / N_HK * 512, 8192, bars + 8 * (n & 7));
          }
        }
      }
    } else if (warp >= 10) {
      if (only_one()) {
        const int q = warp & 1;
#pragma unroll 1
        for (int rb = 0; rb < 16; rb++) {
          mbar_wait(bars + 96 + 8 * q, rb & 1);
#pragma unroll 1
          for (int i = 0; i < 8; i++)
            asm volatile("cp.reduce.async.bulk.global.shared::cta.bulk_group.add.noftz.bf16 [%0], [%1], 4096;"
                         ::"l"(Q.s->img + (size_t)((rb & 7) * N_TILES + T_X1 + (rb >> 3) * 16 + hc * 4 + (i >> 1)) * 1024 + q * 512 + (i & 1) * 256), "r"(sb + 163840 + q * 32768 + i * 4096) : "memory");
          bulk_commit();
          bulk_wait_read();
          mbar_arrive(bars + 80 + 8 * q);
        }
        asm volatile("cp.async.bulk.wait_group 0;" ::: "memory");
        fence_async_glob(); asm volatile("fence.acq_rel.gpu;" ::: "memory");
#pragma unroll 1
        for (int i = 0; i < 8; i++) red_relaxed(Q.s->cnt + i * 32 + G_X1, 8);
      }
    } else if (wg < 2) {
      const uint32_t w = warp & 3;
      uint32_t n = wg * N_HK;
      mbar_wait(bars + 64, 0);
#pragma unroll 1
      for (int rb = 0; rb < 16; rb++) {
        float acc[128];
        mbar_wait(bars + 112 + 8 * wg, (rb & 1) ^ wg ^ 1);
#pragma unroll 1
        for (int kb = 0; kb < N_HK; kb++, n++) {
          mbar_wait(bars + 8 * (n & 7), (n >> 3) & 1);
          const uint32_t da = make_desc(SMEM_BASE + 98304, 16) + (n & 7) * 512, db = make_desc(SMEM_BASE, 8192) + kb * 2048;
          wg_fence();
#pragma unroll
          for (int q = 0; q < 4; q++) wg_n256<H64, H128>(acc, da + qa(q), db + 128 * q, q ? 1 : kb);
          wg_commit();
          wg_wait<1>();
          if (kb && w == 0 && elect_one()) mbar_arrive(bars + 128 + 8 * ((n - 1) & 7));
        }
        if (w == 0 && elect_one()) mbar_arrive(bars + 120 - 8 * wg);
        wg_wait<0>();
        if (w == 0 && elect_one()) mbar_arrive(bars + 128 + 8 * ((n - 1) & 7));
        mbar_wait(bars + 80 + 8 * wg, (rb & 1) ^ 1);
        fence_regs(acc);
        const uint32_t ln = tid_now() & 31, st = sb + 163840 + wg * 32768 + img_pos(w, ln) * 16;
        uint4 gn = lds128(sb + PAR_OFF + (ln & 3) * 16);
#pragma unroll
        for (int c = 0; c < 8; c++) {
          const uint4 g = gn;
          if (c < 7) gn = lds128(sb + PAR_OFF + (c + 1) * 64 + (ln & 3) * 16);
#pragma unroll
          for (int f = 0; f < 2; f++) {
            const float* a = &acc[16 * c + 2 * f];
            sts128(st + c * 4096 + f * 512, hmul2_bf16(g.x, pack_bf16(a[0], a[1])), hmul2_bf16(g.y, pack_bf16(a[4], a[5])),
                   hmul2_bf16(g.z, pack_bf16(a[8], a[9])), hmul2_bf16(g.w, pack_bf16(a[12], a[13])));
          }
        }
        n += N_HK;
        fence_async_smem(); __syncwarp();
        if (elect_one()) mbar_arrive(bars + 96 + 8 * wg);
      }
    }
  } else if (wg < 2) {
    asm volatile("setmaxnreg.inc.sync.aligned.u32 232;");
    const int w = warp & 3, rb = wg * 8 + grp;
    uint4* const img = Q.s->img + (size_t)grp * (N_TILES * 1024);
    uint32_t* const cnt = Q.s->cnt + grp * 32 + wg * 8;
    {
      const uint32_t tid = tid_now() & 127, lane = tid & 31;
      const uint32_t row = 8 * j + 2 * w + (lane >> 4);
      if (tid < 64) st_relaxed_b64(Q.s->stat + ((rb * 2 + rank) * 8 + (j >> 1)) * 64 + tid, 0, 0);
      uint4* dst = img + (T_H + wg * 16 + ((lane >> 3) & 1)) * 1024 + row * 8 + ((lane ^ row) & 7);
      const uint4* back = img + (T_H + wg * 16 + (lane >> 1)) * 1024 + (8 * j + 2 * w + (lane & 1)) * 8;
      const uint32_t tab = sb + TAB_OFF + (lane & 15) * 16;
      if (wg) {
        const uint32_t ep0 = ld_relaxed(&Q.s->ep[cta * 32 + lane]);
        uint32_t* mdst = Q.s->mod0 + ((cta >> 5) * 4 + (cta & 3)) * 512 + ((cta >> 2) & 7) * 64;
        const uint32_t cv = ldg32(Q.c + (cta & 3) * 256 + tid * 2);
        if (tid < 64) st_relaxed(mdst + tid, 0);
        uint4* mbox = Q.s->halo + (size_t)(grp * 16 + j) * 128 + tid;
        st_relaxed_v4(mbox, ~0u, ~0u, ~0u, ~0u); st_relaxed_v4(mbox + 128 * 128, ~0u, ~0u, ~0u, ~0u);
        const uint32_t s0 = ld_relaxed(mbox), s1 = ld_relaxed(mbox + 128 * 128);
        named_sync(0, NTHREADS);
        asm volatile("barrier.cluster.arrive.relaxed.aligned;" ::: "memory");
        in_order();
        sts32(sb + TAB_OFF + 4096 + w * 256 + (lane & 3) * 4 + (((lane >> 2) ^ (2 * w)) << 4), pack_bf16(silu_f(bf_lo(opaque(cv))), silu_f(bf_hi(cv))));
        fence_async_smem();
        if (__any_sync(~0u, (opaque(s0) & opaque(s1)) == 0)) __nanosleep(1);
        named_sync(2, 128);
        asm volatile("barrier.cluster.wait.aligned;" ::: "memory");
        const uint32_t ep = tag_of(opaque(ep0) + 1);
        uint4 xa[4];
#pragma unroll
        for (int i = 0; i < 4; i++) xa[i] = make_uint4(0, 0, 0, 0);
#pragma unroll 1
        for (int s = 0; s < 2; s++) {
          if ((cta >> 6) == s) mod_slice(sb, mdst, ep, w, lane);
          until(t0, s ? T_G1 : T_G0);
          const uint4* ms = (const uint4*)Q.s->mod0 + (2 * s + rank) * 512 + tid;
          uint4 p[4];
#pragma unroll
          for (int i = 0; i < 4; i++) p[i] = make_uint4(0, 0, 0, 0);
          uint32_t it = 0;
          do {
#pragma unroll
            for (int i = 0; i < 4; i++) if (tag_bad(p[i], ep)) p[i] = ld_relaxed_v4(ms + i * 128);
          } while (__any_sync(~0u, tag_bad(p[0], ep) | tag_bad(p[1], ep) | tag_bad(p[2], ep) | tag_bad(p[3], ep)) && ++it < POLL_MAX);
#define F4(f) ((__uint_as_float(p[0].f) + __uint_as_float(p[1].f)) + (__uint_as_float(p[2].f) + __uint_as_float(p[3].f)))
          uint32_t c0 = pack_bf16(F4(x), F4(y)), c1 = pack_bf16(F4(z), F4(w));
#undef F4
          if (w >= 2) { c0 = hadd2_bf16(c0, 0x3f803f80u); c1 = hadd2_bf16(c1, 0x3f803f80u); }
          const uint32_t ta = TAB_OFF + (tid >> 6) * 2048 + (2 * s + rank) * 512 + (tid & 63) * 8, peer = mapa(SMEM_BASE, rank ^ 1);
          asm volatile("st.async.weak.shared::cluster.mbarrier::complete_tx::bytes.v2.b32 [%0], {%2,%3}, [%1];" ::"r"(peer + ta), "r"(peer + BAR_OFF + B_ST + 8 * s), "r"(c0), "r"(c1) : "memory");
          sts64(sb + ta, c0, c1);
          if (s == 0) {
            mbar_wait(bars + B_XB, 0);
#pragma unroll
            for (int i = 0; i < 4; i++) xa[i] = lds128(sb + 4 * 16384 + (row & 7) * 2048 + 1024 + i * 256 + (lane & 15) * 16);
            landed(xa[0].x & xa[1].x & xa[2].x & xa[3].x);
          }
          __syncwarp();
          if (elect_one()) mbar_expect_tx(bars + B_ST + 8 * s, 256);
        }
        mbar_wait(bars + B_ST + 8, 0);
        const float m = __uint_as_float(lds32(sb + TAB_OFF + 6144 + tid * 8)), v = __uint_as_float(lds32(sb + TAB_OFF + 6148 + tid * 8));
#pragma unroll
        for (int i = 4; i < 8; i++) {
          const uint4 a = lds128(tab + i * 256), c = lds128(tab + 2048 + i * 256);
#define NRM(x) pack_bf16(fmaf(bf_lo(x), v, m), fmaf(bf_hi(x), v, m))
          stg128(dst - 16384 + i * 2048, hfma2_bf16(NRM(xa[i & 3].x), c.x, a.x), hfma2_bf16(NRM(xa[i & 3].y), c.y, a.y),
                 hfma2_bf16(NRM(xa[i & 3].z), c.z, a.z), hfma2_bf16(NRM(xa[i & 3].w), c.w, a.w));
#undef NRM
        }
        publish(lane >= 16 ? ld_relaxed(back - 16384) : 0, cnt - 8 + G_H1, 1);
      } else {
        named_sync(0, NTHREADS);
        asm volatile("barrier.cluster.arrive.relaxed.aligned;\nbarrier.cluster.wait.aligned;" ::: "memory");
      }
      mbar_wait(bars + B_XB + 8 * wg, 0);
      float d[64], m = 0.f, v = 0.f, m2 = 0.f, v2 = 0.f;
#pragma unroll
      for (int i = 0; i < 8; i++) {
        const uint4 t = lds128(sb + (4 + wg) * 16384 + (row & 7) * 2048 + i * 256 + (lane & 15) * 16);
        const uint32_t x[4] = {t.x, t.y, t.z, t.w};
#pragma unroll
        for (int e = 0; e < 4; e++) {
          const float d0 = bf_lo(x[e]), d1 = bf_hi(x[e]);
          d[8 * i + 2 * e] = d0; d[8 * i + 2 * e + 1] = d1;
          m += d0; m2 += d1; v = fmaf(d0, d0, v); v2 = fmaf(d1, d1, v2);
        }
      }
      m += m2; v += v2;
#pragma unroll
      for (int i = 1; i < 16; i *= 2) { m += __shfl_xor_sync(~0u, m, i); v += __shfl_xor_sync(~0u, v, i); }
      m *= 1.f / D_;
      v = rsqrtf(fmaxf(fmaf(-m, m, v * (1.f / D_)), 0.f) + 1e-5f);
      m = -m * v;
      if (!wg) {
        sts64(sb + TAB_OFF + 6144 + tid * 8, __float_as_uint(m), __float_as_uint(v));
        __syncwarp();
        if (elect_one()) mbar_arrive(bars + B_ST + 8);
      }
      mbar_wait(bars + B_ST, 0);
#pragma unroll
      for (int s = 0; s < 2; s++) {
        if (s > wg) break;
#pragma unroll
        for (int i = 4 * s; i < 4 * s + 4; i++) {
          const uint4 a = lds128(tab + i * 256), c = lds128(tab + 2048 + i * 256);
#define NRM(e) pack_bf16(fmaf(d[8 * i + 2 * e], v, m), fmaf(d[8 * i + 2 * e + 1], v, m))
          stg128(dst + i * 2048, hfma2_bf16(NRM(0), c.x, a.x), hfma2_bf16(NRM(1), c.y, a.y), hfma2_bf16(NRM(2), c.z, a.z), hfma2_bf16(NRM(3), c.w, a.w));
#undef NRM
        }
      }
      publish(wg || lane < 16 ? ld_relaxed(back) : 0, cnt + G_H0, 1);
    }

    Pipe pp;
    pp.tab = c_cons[wg];
    pp.bars = bars; pp.peer_bars = mapa(bars, rank ^ 1); pp.lead = w == 0; pp.prev = 0; pp.ready = false;
    pp.nx = pp.tab[0];
    const uint32_t dA0 = make_desc(SMEM_BASE, 16), dB0 = make_desc(SMEM_BASE + W_OFF, 8192);
    const uint32_t dAo = dA0 + rank * 512, dAp = dA0 + 512 - rank * 512;

    {
      float acc[2][96];
#pragma unroll 1
      for (int n = 0; n < 14; n++) {
        const uint2 e = pp.begin(n);
        const uint32_t da = dA0 + (e.x & 0xffff), db = dB0 + (e.x >> 16);
        wg_fence();
#pragma unroll
        for (int q = 0; q < 4; q++) {
          wg_n192<H128, H128>(acc[0], da + 2 * q, db + 128 * q, q ? 1 : n);
          wg_n192<H128, H128>(acc[1], da + 2 * q + 512, db + 128 * q, q ? 1 : n);
        }
        wg_commit();
        pp.template end<true>(e.y);
      }
      const uint2 e0 = pp.begin(14), e1 = pp.begin(15);
#pragma unroll
      for (int h = 1; h >= 0; h--) {
        wg_fence();
#pragma unroll
        for (int q = 0; q < 4; q++) wg_n192<H128, H128>(acc[h], dA0 + (e0.x & 0xffff) + 2 * q + 512 * h, dB0 + (e0.x >> 16) + 128 * q, 1);
#pragma unroll
        for (int q = 0; q < 4; q++) wg_n192<H128, H128>(acc[h], dA0 + (e1.x & 0xffff) + 2 * q + 512 * h, dB0 + (e1.x >> 16) + 128 * q, 1);
        wg_commit();
        if (h) { wg_wait<1>(); pp.release(pp.prev); }
      }
      if (pp.lead && elect_one()) mbar_arrive(bars + B_Q + 8 * wg);
      const uint2 ea = pp.begin(16);
      const uint32_t lane = tid_now() & 31, g = lane >> 2, t = lane & 3;
      const uint32_t hal = sb + (ea.x & 0xffff) * 16 + w * 2048 + lane * 16;
      uint4* mbox = Q.s->halo + (size_t)(rb * 16 + j) * 128 + lane;
      const bool first = w == 0 && grp == 0;
      uint32_t qp[2][8][2], kp[2][8][2], vp[2][8][2];
      uint4 hk[2][2], hw[2][2];
#pragma unroll
      for (int h = 1; h >= 0; h--) {
        if (h) wg_wait<1>(); else { in_order(); wg_wait<0>(); pp.release(e0.y); pp.release_now(e1.y); }
        fence_regs(acc[h]);
#pragma unroll
        for (int i = 0; i < 8; i++) {
          kp[h][i][1] = pack_bf16(acc[h][32 + 4 * i + 2], acc[h][32 + 4 * i + 3]);
          vp[h][i][1] = pack_bf16(acc[h][64 + 4 * i + 2], acc[h][64 + 4 * i + 3]);
        }
        if (h == 1 && w == 3 && grp < 7) {
#pragma unroll
          for (int d = 0; d < 2; d++) {
            st_relaxed_v4(mbox + 16 * 128 + d * 32, kp[h][4 * d][1], kp[h][4 * d + 1][1], kp[h][4 * d + 2][1], kp[h][4 * d + 3][1]);
            st_relaxed_v4(mbox + 16 * 128 + d * 32 + 64, vp[h][4 * d][1], vp[h][4 * d + 1][1], vp[h][4 * d + 2][1], vp[h][4 * d + 3][1]);
          }
        }
        if (h == 0) {
#pragma unroll
          for (int d = 0; d < 2; d++) {
            hk[0][d] = hw[0][d] = make_uint4(0, 0, 0, 0);
            if (w == 0) { hk[0][d] = ld_relaxed_v4(mbox + d * 32); hw[0][d] = ld_relaxed_v4(mbox + d * 32 + 64); }
          }
        }
#pragma unroll
        for (int i = 0; i < 8; i++) vp[h][i][1] = movm(vp[h][i][1]);
        if (h == 0 || w < 3) {
#pragma unroll
          for (int d = 0; d < 2; d++) {
            sts128(hal + 2048 + h * 8192 + d * 1024, kp[h][4 * d][1], kp[h][4 * d + 1][1], kp[h][4 * d + 2][1], kp[h][4 * d + 3][1]);
            sts128(hal + 2048 + h * 8192 + d * 1024 + 512, vp[h][4 * d][1], vp[h][4 * d + 1][1], vp[h][4 * d + 2][1], vp[h][4 * d + 3][1]);
          }
        }
        if (h == 0) {
          named_sync(1 + wg, 128);
#pragma unroll
          for (int d = 0; d < 2; d++) {
            if (w) { hk[0][d] = lds128(hal + d * 1024); hw[0][d] = lds128(hal + d * 1024 + 512); }
            hk[1][d] = lds128(hal + 8192 + d * 1024); hw[1][d] = lds128(hal + 8192 + d * 1024 + 512);
          }
        }
#pragma unroll
        for (int i = 0; i < 8; i++) {
          kp[h][i][0] = opaque(pack_bf16(acc[h][32 + 4 * i], acc[h][32 + 4 * i + 1]));
          vp[h][i][0] = movm(pack_bf16(acc[h][64 + 4 * i], acc[h][64 + 4 * i + 1]));
          qp[h][i][0] = opaque(pack_bf16(acc[h][4 * i], acc[h][4 * i + 1]));
          qp[h][i][1] = opaque(pack_bf16(acc[h][4 * i + 2], acc[h][4 * i + 3]));
        }
      }
      if (w == 0) {
        for (uint32_t it = 0; grp > 0 && it < POLL_MAX && __any_sync(~0u, empty(hk[0][0]) || empty(hk[0][1]) || empty(hw[0][0]) || empty(hw[0][1])); it++) {
#pragma unroll
          for (int d = 0; d < 2; d++) { hk[0][d] = ld_relaxed_v4(mbox + d * 32); hw[0][d] = ld_relaxed_v4(mbox + d * 32 + 64); }
        }
#pragma unroll
        for (int d = 0; d < 2; d++)
          hw[0][d] = first ? make_uint4(0, 0, 0, 0) : make_uint4(movm(hw[0][d].x), movm(hw[0][d].y), movm(hw[0][d].z), movm(hw[0][d].w));
      }
      const uint32_t hv[2][8] = {{hw[0][0].x, hw[0][0].y, hw[0][0].z, hw[0][0].w, hw[0][1].x, hw[0][1].y, hw[0][1].z, hw[0][1].w},
                                 {hw[1][0].x, hw[1][0].y, hw[1][0].z, hw[1][0].w, hw[1][1].x, hw[1][1].y, hw[1][1].z, hw[1][1].w}};
      landed(hw[0][0].x & hw[0][1].x & hw[1][0].x & hw[1][1].x);
      float s0[4][4], s1[4][4], s2[4][4];
#pragma unroll
      for (int c = 3; c >= 0; c--) {
        const int h = c >> 1, b = (c & 1) * 4;
        mma16816z(s1[c], qp[h][b][0], qp[h][b][1], qp[h][b + 1][0], qp[h][b + 1][1], kp[h][b][0], kp[h][b + 1][0]);
        mma16816z(s2[c], qp[h][b][0], qp[h][b][1], qp[h][b + 1][0], qp[h][b + 1][1], kp[h][b][1], kp[h][b + 1][1]);
        mma16816z(s0[c], qp[h][b][0], qp[h][b][1], qp[h][b + 1][0], qp[h][b + 1][1], hk[h][c & 1].x, hk[h][c & 1].y);
      }
#pragma unroll
      for (int c = 3; c >= 0; c--) {
        const int h = c >> 1, b = (c & 1) * 4 + 2;
        mma16816(s1[c], qp[h][b][0], qp[h][b][1], qp[h][b + 1][0], qp[h][b + 1][1], kp[h][b][0], kp[h][b + 1][0]);
        mma16816(s2[c], qp[h][b][0], qp[h][b][1], qp[h][b + 1][0], qp[h][b + 1][1], kp[h][b][1], kp[h][b + 1][1]);
        mma16816(s0[c], qp[h][b][0], qp[h][b][1], qp[h][b + 1][0], qp[h][b + 1][1], hk[h][c & 1].z, hk[h][c & 1].w);
      }
      arrive_after(bars + B_R + 16 * wg, s0[0][0]);
      const bool c0 = 2 * t <= g, c1 = 2 * t + 1 <= g;
      const uint32_t mcur = (c0 ? 0x0000ffffu : 0u) | (c1 ? 0xffff0000u : 0u);
      uint32_t pa[4], pb[4];
#pragma unroll
      for (int c = 3; c >= 0; c--) {
        if (c < 2 && first) { s0[c][0] = -INFINITY; s0[c][1] = -INFINITY; }
        float a0 = c0 ? s1[c][0] : s0[c][0], a1 = c1 ? s1[c][1] : s0[c][1];
        float b0 = c0 ? s2[c][2] : s1[c][2], b1 = c1 ? s2[c][3] : s1[c][3];
        const float ma = quad_max(fmaxf(a0, a1)), mb = quad_max(fmaxf(b0, b1));
        a0 = ex2((a0 - ma) * ATT_SCALE_LOG2E); a1 = ex2((a1 - ma) * ATT_SCALE_LOG2E);
        b0 = ex2((b0 - mb) * ATT_SCALE_LOG2E); b1 = ex2((b1 - mb) * ATT_SCALE_LOG2E);
        const float ia = rcp(quad_sum(a0 + a1)), ib = rcp(quad_sum(b0 + b1));
        pa[c] = opaque(pack_bf16(a0 * ia, a1 * ia)); pb[c] = opaque(pack_bf16(b0 * ib, b1 * ib));
      }
      if (pp.lead) { mbar_wait(bars + B_R + 16 * wg, 0); pp.release(ea.y); }
      float o[16][4];
#pragma unroll
      for (int i = 0; i < 16; i++) mma16816z(o[i], pa[i >> 2] & mcur, pb[i >> 2] & ~mcur, 0u, pb[i >> 2] & mcur, vp[i >> 3][i & 7][0], vp[i >> 3][i & 7][1]);
#pragma unroll
      for (int i = 0; i < 16; i++) mma1688(o[i], pa[i >> 2] & ~mcur, 0u, hv[i >> 3][i & 7]);
      arrive_after(bars + B_R + 16 * wg + 8, o[15][0]);
      uint4* tile = img + (T_O + wg * 16 + j) * 1024;
      uint4* dst = tile + img_pos(w, lane);
#pragma unroll
      for (int c = 0; c < 4; c++)
#pragma unroll
        for (int f = 0; f < 2; f++) {
          stg128(dst + c * 256 + f * 32, pack_bf16(o[4 * c][2 * f], o[4 * c][2 * f + 1]), pack_bf16(o[4 * c + 1][2 * f], o[4 * c + 1][2 * f + 1]),
                 pack_bf16(o[4 * c + 2][2 * f], o[4 * c + 2][2 * f + 1]), pack_bf16(o[4 * c + 3][2 * f], o[4 * c + 3][2 * f + 1]));
        }
      publish(ld_relaxed(tile + img_line(w, lane)), cnt + G_O, 1);
    }

    {
      float acc[2][64];
      uint32_t xr[32];
      {
        const uint32_t lane = tid_now() & 31;
        const uint2 e = pp.begin(17);
        const uint32_t a0 = sb + (e.x & 0xffff) * 16 + (w * 16 + (lane & 15)) * 128 + (((lane >> 4) ^ (lane & 7)) << 4);
#pragma unroll
        for (int i = 0; i < 8; i++) ldsm4((a0 ^ ((i & 3) << 5)) + (i >> 2) * 8192, xr[4 * i], xr[4 * i + 1], xr[4 * i + 2], xr[4 * i + 3]);
        landed(xr[0] & xr[4] & xr[8] & xr[12] & xr[16] & xr[20] & xr[24] & xr[28]);
        named_sync(1 + wg, 128);
        pp.release(e.y);
      }
      pp.prev = 0;
#pragma unroll 1
      for (int n = 18; n < 24; n++) {
        const uint2 e = pp.begin(n);
        const uint32_t da = e.x & 0xffff, db = dB0 + (e.x >> 16);
        wg_fence();
#pragma unroll
        for (int q = 0; q < 4; q++) {
          wg_n128<H64, H128>(acc[0], dAo + da + qa(q), db + 128 * q, q ? 1 : n - 18);
          wg_n128<H64, H128>(acc[1], dAp + da + qa(q), db + 128 * q, q ? 1 : n - 18);
        }
        wg_commit();
        pp.template end<true>(e.y);
      }
      const uint2 e0 = pp.begin(24);
      const uint2 e1 = pp.begin(25);
#pragma unroll
      for (int h = 1; h >= 0; h--) {
        wg_fence();
#pragma unroll
        for (int q = 0; q < 4; q++) wg_n128<H64, H128>(acc[h], (h ? dAp : dAo) + (e0.x & 0xffff) + qa(q), dB0 + (e0.x >> 16) + 128 * q, 1);
#pragma unroll
        for (int q = 0; q < 4; q++) wg_n128<H64, H128>(acc[h], (h ? dAp : dAo) + (e1.x & 0xffff) + qa(q), dB0 + (e1.x >> 16) + 128 * q, 1);
        wg_commit();
      }
      const uint32_t tid = tid_now() & 127, lane = tid & 31;
      const uint2 ea = pp.begin(26);
      const uint32_t px = (ea.x & 0xffff) * 16 + tid * 16;
      wg_wait<1>();
      pp.release_now(pp.prev);
      fence_regs(acc[1]);
#pragma unroll
      for (int i = 0; i < 8; i++)
        st_async(pp.peer_bars - BAR_OFF + px + i * 2048, pp.peer_bars + (pp.nx.y & 0x3ff), pack_bf16(acc[1][8 * i], acc[1][8 * i + 1]), pack_bf16(acc[1][8 * i + 2], acc[1][8 * i + 3]),
                 pack_bf16(acc[1][8 * i + 4], acc[1][8 * i + 5]), pack_bf16(acc[1][8 * i + 6], acc[1][8 * i + 7]));
      wg_wait<0>();
      pp.release(e0.y); pp.release(e1.y); pp.release_now(ea.y);
      fence_regs(acc[0]);
      const uint32_t ep = tag_of(lds32(bars + ROLE_OFF + 4));
      mbar_wait(bars + B_PAR, 0);
      uint32_t pr[3][16];
#pragma unroll
      for (int i = 0; i < 4; i++) {
        const uint4 x = lds128(sb + PAR_OFF + (i >> 2) * 256 + (lane & 3) * 64 + (i & 3) * 16);
        pr[i >> 2][(i & 3) * 4] = x.x; pr[i >> 2][(i & 3) * 4 + 1] = x.y; pr[i >> 2][(i & 3) * 4 + 2] = x.z; pr[i >> 2][(i & 3) * 4 + 3] = x.w;
      }
      const uint2 eb = pp.begin(27);
      float sm[2] = {0.f, 0.f}, sq[2] = {0.f, 0.f};
#pragma unroll
      for (int c = 0; c < 8; c++) {
        const uint4 z = lds128(sb + px + c * 2048);
        const uint32_t zz[4] = {z.x, z.y, z.z, z.w};
#pragma unroll
        for (int b = 0; b < 4; b++) {
          const int i = 4 * c + b;
          xr[i] = hfma2_bf16(pr[0][i >> 1], hadd2_bf16(pack_bf16(acc[0][2 * i], acc[0][2 * i + 1]), zz[b]), xr[i]);
          const float d0 = bf_lo(xr[i]), d1 = bf_hi(xr[i]);
          acc[0][2 * i] = d0; acc[0][2 * i + 1] = d1;
          sm[i & 1] += d0 + d1;
          sq[i & 1] = fmaf(d0, d0, fmaf(d1, d1, sq[i & 1]));
        }
      }
      {
        const bool b0 = lane & 1;
        sm[0] = (b0 ? sm[1] : sm[0]) + __shfl_xor_sync(~0u, b0 ? sm[0] : sm[1], 1);
        sq[0] = (b0 ? sq[1] : sq[0]) + __shfl_xor_sync(~0u, b0 ? sq[0] : sq[1], 1);
        sm[0] += __shfl_xor_sync(~0u, sm[0], 2);
        sq[0] += __shfl_xor_sync(~0u, sq[0], 2);
      }
      uint2* ss = Q.s->stat + (rb * 2 + rank) * 512 + w * 16 + (lane >> 2) * 2 + (lane & 1);
      if (!(lane & 2)) st_relaxed_b64(ss + (j >> 1) * 64, tagf(sm[0], ep), tagf(sq[0], ep));
      named_sync(1 + wg, 128);
      pp.release(eb.y);
      mbar_wait(bars + B_PAR + 8, 0);
#pragma unroll
      for (int i = 4; i < 12; i++) {
        const uint4 x = lds128(sb + PAR_OFF + (i >> 2) * 256 + (lane & 3) * 64 + (i & 3) * 16);
        pr[i >> 2][(i & 3) * 4] = x.x; pr[i >> 2][(i & 3) * 4 + 1] = x.y; pr[i >> 2][(i & 3) * 4 + 2] = x.z; pr[i >> 2][(i & 3) * 4 + 3] = x.w;
      }
      {
        ss += (lane & 2) * 128;
        uint2 p[4];
#pragma unroll
        for (int i = 0; i < 4; i++) p[i] = make_uint2(0, 0);
        spin(DELAY_ST);
        uint32_t it = 0, bad;
        do {
          bad = 0;
#pragma unroll
          for (int i = 0; i < 4; i++) if (((p[i].x ^ ep) | (p[i].y ^ ep)) & 3u) p[i] = ld_relaxed_b64(ss + i * 64);
#pragma unroll
          for (int i = 0; i < 4; i++) bad |= (p[i].x ^ ep) | (p[i].y ^ ep);
        } while (__any_sync(~0u, bad & 3u) && ++it < POLL_MAX);
        float m = (__uint_as_float(p[0].x) + __uint_as_float(p[1].x)) + (__uint_as_float(p[2].x) + __uint_as_float(p[3].x));
        float v = (__uint_as_float(p[0].y) + __uint_as_float(p[1].y)) + (__uint_as_float(p[2].y) + __uint_as_float(p[3].y));
        m += __shfl_xor_sync(~0u, m, 2); v += __shfl_xor_sync(~0u, v, 2);
        m *= 1.f / D_;
        v = rsqrtf(fmaxf(fmaf(-m, m, v * (1.f / D_)), 0.f) + 1e-5f);
        m = -m * v;
#pragma unroll
        for (int r = 0; r < 2; r++) { sm[r] = __shfl_sync(~0u, m, r, 2); sq[r] = __shfl_sync(~0u, v, r, 2); }
      }
      uint4* tile = img + (T_H + wg * 16 + (j & 14)) * 1024 + rank * 512;
      uint4* dst = tile + img_pos(w, lane);
#pragma unroll
      for (int c = 0; c < 4; c++)
#pragma unroll
        for (int f = 0; f < 2; f++) {
          uint32_t y[4];
#pragma unroll
          for (int b = 0; b < 4; b++) {
            const int i = c * 4 + b;
            y[b] = hfma2_bf16(pack_bf16(fmaf(acc[0][4 * i + 2 * f], sq[f], sm[f]), fmaf(acc[0][4 * i + 2 * f + 1], sq[f], sm[f])), pr[2][i], pr[1][i]);
          }
          stg128(dst + (c >> 1) * 1024 + (c & 1) * 256 + f * 32, y[0], y[1], y[2], y[3]);
        }
      publish(ld_relaxed(tile + img_line(w, lane) + (lane >> 4) * 512), cnt + G_H2, 1);
#pragma unroll
      for (int c = 0; c < 4; c++)
#pragma unroll
        for (int f = 0; f < 2; f++) {
          stg128(dst + (T_X1 - T_H + (c >> 1)) * 1024 + (c & 1) * 256 + f * 32, xr[8 * c + f], xr[8 * c + 2 + f], xr[8 * c + 4 + f], xr[8 * c + 6 + f]);
        }
    }

    float acc[2][64], ax[32];
    uint32_t px_y;
    {
      float a3[2][96];
      pp.prev = 0;
#pragma unroll 1
      for (int n = 28; n < 44; n++) {
        const uint2 e = pp.begin(n);
        const uint32_t da = e.x & 0xffff, db = dB0 + (e.x >> 16);
        wg_fence();
#pragma unroll
        for (int q = 0; q < 4; q++) {
          wg_n192<H64, H128>(a3[0], dAo + da + qa(q), db + 128 * q, q ? 1 : n - 28);
          wg_n192<H64, H128>(a3[1], dAp + da + qa(q), db + 128 * q, q ? 1 : n - 28);
        }
        wg_commit();
        pp.end(e.y);
      }
      px_y = pp.nx.y;
      pp.nx = pp.tab[45]; pp.ready = false;
      mbar_wait(bars + ((px_y >> 16) & 0x7ff), px_y >> 31);
      wg_wait<0>();
      pp.release_now(pp.prev);
      fence_regs(a3[0]); fence_regs(a3[1]);
      pp.prev = 0;
#pragma unroll
      for (int i = 0; i < 4; i++)
        st_async(pp.peer_bars - 8192 + (tid_now() & 127) * 16 + i * 2048, pp.peer_bars + (px_y & 0x3ff), pack_bf16(a3[1][64 + 8 * i], a3[1][65 + 8 * i]),
                 pack_bf16(a3[1][66 + 8 * i], a3[1][67 + 8 * i]), pack_bf16(a3[1][68 + 8 * i], a3[1][69 + 8 * i]), pack_bf16(a3[1][70 + 8 * i], a3[1][71 + 8 * i]));
#pragma unroll
      for (int i = 0; i < 64; i++) { acc[0][i] = a3[0][i]; acc[1][i] = a3[1][i]; }
#pragma unroll
      for (int i = 0; i < 32; i++) ax[i] = a3[0][64 + i];
    }
    uint32_t seen, seen2;
#pragma unroll 1
    for (int T = 0;; T++) {
      wg_wait<0>();
      pp.release_now(pp.prev);
      fence_regs(acc[0]); fence_regs(acc[1]);
      pp.prev = 0;
      {
        const uint32_t lane = tid_now() & 31;
        uint4* tile = img + (T_ACT + wg * 56 + (T ? 8 + 16 * T : 0) + j) * 1024;
        uint4* tx = img + (T_ACT + wg * 56 + 16 + (j >> 1)) * 1024 + rank * 512;
        const int ts = (int)clock();
#pragma unroll
        for (int c = 0; c < 4; c++)
#pragma unroll
          for (int f = 0; f < 2; f++) {
            uint32_t y[4];
#pragma unroll
            for (int b = 0; b < 4; b++) {
              const int i = ((c & 1) * 4 + b) * 4 + 2 * f;
              y[b] = pack_bf16(swiglu(acc[c >> 1][i], acc[c >> 1][i] * acc[c >> 1][32 + i]), swiglu(acc[c >> 1][i + 1], acc[c >> 1][i + 1] * acc[c >> 1][33 + i]));
            }
            stg128(tile + img_pos(w, lane) + ((c >> 1) ^ rank) * 512 + (c & 1) * 256 + f * 32, y[0], y[1], y[2], y[3]);
            if (c + f < 4) until(ts, (2 * c + f + 1) * P_ACT);
            fence_regs(acc[0]); fence_regs(acc[1]);
          }
        if (T == 0) {
          if (wg == 0 && j < N_HK) publish(ld_relaxed(tile + img_line(w, lane)), cnt + G_HK, 1);
          mbar_wait(bars + (px_y & 0x3ff), 1);
          uint32_t z[16];
#pragma unroll
          for (int i = 0; i < 4; i++) { const uint4 x = lds128(bars - 8192 + (tid_now() & 127) * 16 + i * 2048); z[4 * i] = x.x; z[4 * i + 1] = x.y; z[4 * i + 2] = x.z; z[4 * i + 3] = x.w; }
          landed(z[0] & z[4] & z[8] & z[12]);
          named_sync(1 + wg, 128);
          pp.release(px_y);
#pragma unroll
          for (int c = 0; c < 2; c++)
#pragma unroll
            for (int f = 0; f < 2; f++) {
              uint32_t y[4];
#pragma unroll
              for (int b = 0; b < 4; b++) {
                const int i = (c * 4 + b) * 2 + f;
                const float o0 = bf_lo(z[i]), o1 = bf_hi(z[i]);
                y[b] = pack_bf16(swiglu(rank ? o0 : ax[2 * i], o0 * ax[2 * i]), swiglu(rank ? o1 : ax[2 * i + 1], o1 * ax[2 * i + 1]));
              }
              stg128(tx + img_pos(w, lane) + c * 256 + f * 32, y[0], y[1], y[2], y[3]);
            }
        }
        seen = ld_relaxed(tile + img_line(w, lane));
        seen2 = ld_relaxed(tx + img_line(w, lane & 15));
      }
      if (T == 2) break;
      const int n0 = 45 + 16 * T, n1 = n0 + 16;
#pragma unroll 1
      for (int n = n0; n < n1; n++) {
        const uint2 e = pp.begin(n);
        const uint32_t da = e.x & 0xffff, db = dB0 + (e.x >> 16);
        wg_fence();
#pragma unroll
        for (int q = 0; q < 4; q++) {
          wg_n128<H64, H128>(acc[0], dAo + da + qa(q), db + 128 * q, q ? 1 : n - n0);
          wg_n128<H64, H128>(acc[1], dAp + da + qa(q), db + 128 * q, q ? 1 : n - n0);
        }
        wg_commit();
        if (n == n0 + 1) publish(opaque(seen) & opaque(seen2), cnt + G_ACT + T, 1);
        pp.end(e.y);
      }
    }
    {
      uint32_t gp[16];
#pragma unroll
      for (int ph = 0; ph < 2; ph++) {
#pragma unroll 1
        for (int n = ph ? 90 : 77; n < (ph ? N_END : 90); n++) {
          const uint2 e = pp.begin(n);
          const uint32_t da = dA0 + wg * 512 + (e.x & 0xffff), db = dB0 + (e.x >> 16);
          wg_fence();
#pragma unroll
          for (int q = 0; q < 4; q++) wg_n128<H64, H128>(acc[0], da + qa(q), db + 128 * q, q || ph ? 1 : n - 77);
          wg_commit();
          pp.end(e.y);
        }
        if (ph == 0) {
          publish(opaque(seen) & opaque(seen2), cnt + G_ACT + 2, 1);
          mbar_wait(bars + B_GB, 0);
#pragma unroll
          for (int i = 0; i < 4; i++) {
            const uint4 x = lds128(sb + PAR_OFF + 768 + (tid_now() & 3) * 64 + i * 16);
            gp[4 * i] = x.x; gp[4 * i + 1] = x.y; gp[4 * i + 2] = x.z; gp[4 * i + 3] = x.w;
          }
        }
      }
      const uint32_t lane = tid_now() & 31;
      uint32_t xp[32];
      {
        const uint2 e0 = pp.begin(N_END), e1 = pp.begin(N_END + 1);
#pragma unroll
        for (int i = 0; i < 8; i++) {
          const uint4 r = lds128(sb + (((i & 4 ? e1.x : e0.x) & 0xffff) + wg * 512 + img_pos(w, lane) + ((i >> 1) & 1) * 256 + (i & 1) * 32) * 16);
          xp[(i >> 1) * 8 + (i & 1)] = r.x; xp[(i >> 1) * 8 + 2 + (i & 1)] = r.y; xp[(i >> 1) * 8 + 4 + (i & 1)] = r.z; xp[(i >> 1) * 8 + 6 + (i & 1)] = r.w;
        }
      }
      const uint32_t st = sb + ((w & 2) ? pp.nx.x >> 16 : pp.nx.x & 0xffff) * 16 + wg * 8192 + (w & 1) * 4096;
      const uint32_t a0 = opaque(st + (lane & 15) * 128 + (((lane >> 4) ^ (lane & 7)) << 4));
      if (pp.lead && elect_one()) mbar_arrive(bars + B_END);
      wg_wait<0>();
      pp.release_now(pp.prev);
      fence_regs(acc[0]);
#pragma unroll
      for (int c = 0; c < 4; c++) {
        uint32_t y[2][4];
#pragma unroll
        for (int f = 0; f < 2; f++)
#pragma unroll
          for (int b = 0; b < 4; b++) {
            const int i = 16 * c + 4 * b + 2 * f;
            y[f][b] = hfma2_bf16(gp[4 * c + b], pack_bf16(acc[0][i], acc[0][i + 1]), xp[8 * c + 2 * b + f]);
          }
        stsm4((a0 ^ ((c & 1) << 6)) + (c >> 1) * 2048, y[0][0], y[1][0], y[0][1], y[1][1]);
        stsm4((a0 ^ ((c & 1) << 6) ^ 32) + (c >> 1) * 2048, y[0][2], y[1][2], y[0][3], y[1][3]);
        if (c == 1) {
          fence_async_smem(); __syncwarp();
          if (elect_one()) {
            tma2d_st(&P.mOut, st, typ * D_ + (j & 7) * 128, grp * 128 + wg * 64 + w * 16);
            bulk_commit();
          }
        }
      }
      {
        __syncwarp();
        const uint32_t ln = tid_now() & 31;
        uint4* op = (uint4*)(Q.out + (size_t)(grp * 256 + 2 * (wg * 64 + w * 16 + (ln >> 3)) + typ) * D_ + (j & 7) * 128 + 64) + (ln & 7);
        uint4 r[4];
#pragma unroll
        for (int k = 0; k < 4; k++) r[k] = lds128(st + 2048 + ((ln >> 3) + 4 * k) * 128 + (((ln & 7) ^ (((ln >> 3) + 4 * k) & 7)) << 4));
#pragma unroll
        for (int k = 0; k < 4; k++) stg128(op + k * D_, r[k].x, r[k].y, r[k].z, r[k].w);
        if (elect_one()) bulk_wait_read();
      }
    }
  } else {
    asm volatile("setmaxnreg.dec.sync.aligned.u32 40;");
    const uint32_t lane = tid_now() & 31;
    if (elect_one()) {
      if (warp == 10) {
        prefetch_tmap(&P.mWqkv);
#pragma unroll
        for (int i = 0; i < 12; i++) mbar_init(bars + 1024 + 8 * i, i < 4 ? 4 : 1);
        mbar_init(bars + B_ST, 4); mbar_init(bars + B_ST + 8, 8); mbar_init(bars + B_XB, 1); mbar_init(bars + B_XB + 8, 1); mbar_init(bars + B_END, 2);
        sts32(bars + ROLE_OFF, cta >> 1);
      } else if (warp == 11) {
#pragma unroll 1
        for (int u = 0; u < 2; u++) {
#pragma unroll
          for (int i = 0; i < 20; i++) mbar_init(bars + u * 512 + 352 + 8 * i, 1 + u);
        }
      } else {
#pragma unroll 22
        for (int i = 0; i < 44; i++) mbar_init(bars + (warp & 1) * 512 + 8 * i, 1 + (warp & 1));
      }
      asm volatile("fence.mbarrier_init.release.cluster;" ::: "memory");
    }
    named_sync(0, NTHREADS);
    asm volatile("barrier.cluster.arrive.relaxed.aligned;" ::: "memory");
    asm volatile("barrier.cluster.wait.aligned;" ::: "memory");
    const uint32_t ep0 = ld_relaxed(&Q.s->ep[cta * 32 + lane]);
    if (!(warp & 1)) {
      if (only_one()) {
        const int q = (warp >> 1) & 1;
        const uint2* tab = c_act[q];
        const char* src = (const char*)(Q.s->img + (size_t)grp * (N_TILES * 1024) + rank * 512);
        const uint32_t sa = sb + rank * 8192;
        if (q) {
          if (cta >= 64) {
#pragma unroll 1
            for (int i = 0; i < 4; i++) {
              until(t0, (cta >= 96 ? T_Q3 : T_Q2) + i * P_Q);
              mbar_expect_tx(bars + B_SL + 8 * i, 8192);
              tma2d_once(sb + SL_OFF + i * 8192, &P.mWm2, bars + B_SL + 8 * i, ((cta >> 4) & 1) * D_ + (cta >> 5) * 256 + ((cta >> 2) & 3) * 64, (cta & 3) * 256 + i * 64);
            }
          }
        }
        mbar_expect_tx(bars + B_XB + 8 * q, 16384);
#pragma unroll 1
        for (int i = 0; i < 8; i++) {
          until(t0, q ? T_XB + i * P_XB : T_XA);
          bulk_g2s(sb + (4 + q) * 16384 + i * 2048, Q.x + (size_t)(cta * 16 + 2 * i + q) * D_, 2048, bars + B_XB + 8 * q);
        }
        const uint32_t target = (opaque(ep0) + 1) * 64;
        const uint32_t* cnt = Q.s->cnt + grp * 32;
        const char* x1 = src + (T_X1 + typ * 16 + (j & 7) * 2) * 16384 + (q - rank) * 8192;
        uint2 nx = tab[0];
#pragma unroll 1
        for (int ph = 0; ph < 4; ph++) {
          const bool half = ph == 3;
          tiles<1>(bars, tab, nx, half ? 77 : (ph ? 11 + 17 * ph : 0), half ? N_END : (ph ? 11 + 33 * ph : 16), half ? sb + q * 8192 + rank * 4096 : sa,
                   half ? src + typ * 56 * 16384 + q * 8192 - rank * 4096 : src, half ? 4096 : 8192, half ? cnt + typ * 8 : cnt, target, 0, 0);
          if (ph == 1) { mbar_expect_tx(bars + (nx.y & 0x3ff), 8192); nx = tab[45]; }
          if (ph) continue;
#pragma unroll 1
          for (int n = 16; n < 28; n++) {
            const uint2 e = nx;
            nx = tab[n + 1];
            const uint32_t fb = bars + (e.y & 0x3ff);
            mbar_wait(bars + (e.x & 0x7ff), e.x >> 31);
            mbar_expect_tx(fb, (e.y >> 29) << 13);
            if (n == 17) {
              tma2d(sb + (e.y & 0x3c000), &P.mX, fb, q * D_ + (j & 14) * 64, grp * 128 + rank * 64);
              tma2d(sb + (e.y & 0x3c000) + 8192, &P.mX, fb, q * D_ + (j | 1) * 64, grp * 128 + rank * 64);
              tiles<0>(bars, tab, nx, 18, 26, sb, src + rank * 8192, 16384, cnt, target, q ? P_G2B : P_G2, q ? F_G2B : F_G2A);
              n = 25;
            }
          }
        }
        while ((int32_t)(ld_relaxed_line(cnt + G_X1) - target) < 0) {}
        asm volatile("fence.acquire.gpu;" ::: "memory"); fence_async_glob();
#pragma unroll 1
        for (int n = 0; n < 2; n++) {
          const uint2 e = tab[N_END + n];
          const uint32_t fb = bars + (e.y & 0x3ff);
          mbar_expect_tx(fb, 8192);
          mbar_wait(bars + (e.x & 0x7ff), e.x >> 31);
          bulk_g2s(sb + q * 8192 + (e.y & 0x3c000), x1 + n * 16384, 8192, fb);
        }
      }
    } else if (warp == 9) {
      if (only_one()) {
        uint2 nx = c_w[0][0];
#pragma unroll 1
        for (int n = 0; n < N_W;) {
          if (n < 5) until(t0, n ? T_W + (n - 1) * P_W : T_W0);
          if (n == 2) mbar_wait(bars + B_SLE, 0);
          if (n == 5) { prefetch_tmap(&P.mWo); prefetch_tmap(&P.mWg); prefetch_tmap(&P.mWu); prefetch_tmap(&P.mWd); prefetch_tmap(&P.mX); }
          const int u = (nx.y >> 10) & 7;
          if (u < 2) {
            weights<3>(sb, nx, n, u ? &P.mWg : &P.mWqkv, u ? &P.mWu : &P.mWqkv, u ? &P.mWg + rank : &P.mWqkv,
                       j * 64, (u ? 0 : D_) + j * 64, u ? 1024 + (j >> 1) * 64 : 2 * D_ + j * 64, 0);
          } else {
            const bool ffn = u == 3 || u == 4;
            const int c0 = ffn ? u * 1024 - 1536 + j * 64 : (u == 2 ? j >> 1 : j & 7) * 128;
            const CUtensorMap* m0 = ffn ? &P.mWg : (u == 2 ? &P.mWo : &P.mWd);
            weights<2>(sb, nx, n, m0, m0 + ffn, nullptr, c0, ffn ? c0 : c0 + 64, 0, u == 2 ? rank * 2 : 0);
          }
        }
        prefetch_tmap(&P.mOut);
      }
    } else {
      {
        const uint32_t i = opaque((grp * 2 + rank) * 8), k = i < N_W - 128 ? i + 128 : 128;
        if ((c_cons[0][i].x & c_cons[1][i].x & c_act[0][i].y & c_act[1][i].y & c_w[0][i].y & c_w[0][k].y) == 0xffffffffu) __trap();
      }
      const uint32_t ep = opaque(ep0) + 1;
      if (lane == 0) {
        sts32(bars + ROLE_OFF + 4, ep);
        uint32_t pr; asm volatile("ld.shared::cluster.u32 %0, [%1];" : "=r"(pr) : "r"(mapa(bars + ROLE_OFF, rank ^ 1)) : "memory");
        if (pr != (uint32_t)(cta >> 1) || sb != smem_u32(smem_raw)) { __trap(); }
      }
      const uint32_t tag = tag_of(ep);
#pragma unroll 1
      for (int i = 0; i < 8; i++) {
        const uint2* src = (const uint2*)(Q.s->modp + (i >> 1) * 1024 + (i < 6 ? j >> 1 : j & 7) * 128 + (i & 1) * 64) + lane;
        uint2 a; uint32_t it = 0;
        do { if (it) __nanosleep(200); a = ld_relaxed_b64(src); guard(++it); } while (__any_sync(~0u, ((a.x ^ tag) | (a.y ^ tag)) & 3u));
        uint32_t p = pack_bf16(__uint_as_float(a.x), __uint_as_float(a.y));
        if ((i >> 1) == 2) p = pack_bf16(1.f + bf_lo(p), 1.f + bf_hi(p));
        const float sc = i < 2 ? 1.f : (i < 6 ? 0.5f : 2.f);
        p = pack_bf16(sc * bf_lo(p), sc * bf_hi(p));
        sts32(sb + PAR_OFF + (i >> 1) * 256 + (lane & 3) * 64 + (i & 1) * 32 + (lane >> 2) * 4, p);
        __syncwarp();
        if ((i == 1 || i == 5 || i == 7) && elect_one()) { mbar_arrive(bars + (i == 7 ? B_GB : B_PAR + (i & 4) * 2)); }
      }
      mbar_wait_bounded(bars + B_R, 0);
      Q.s->ep[cta * 32 + lane] = ep;
      mbar_wait_bounded(bars + B_END, 0);
    }
  }
}

typedef CUresult (*PFN_encodeTiled)(CUtensorMap*, CUtensorMapDataType, cuuint32_t, void*, const cuuint64_t*, const cuuint64_t*,
                                    const cuuint32_t*, const cuuint32_t*, CUtensorMapInterleave, CUtensorMapSwizzle,
                                    CUtensorMapL2promotion, CUtensorMapFloatOOBfill);

void make_map(PFN_encodeTiled enc, CUtensorMap* m, const void* ptr, uint64_t inner, uint64_t outer, uint32_t box_outer, int promo = CU_TENSOR_MAP_L2_PROMOTION_L2_256B) {
  cuuint64_t dims[2] = {inner, outer};
  cuuint64_t strides[1] = {inner * 2};
  cuuint32_t box[2] = {64, box_outer};
  cuuint32_t es[2] = {1, 1};
  enc(m, CU_TENSOR_MAP_DATA_TYPE_BFLOAT16, 2, const_cast<void*>(ptr), dims, strides, box, es, CU_TENSOR_MAP_INTERLEAVE_NONE,
      CU_TENSOR_MAP_SWIZZLE_128B, (CUtensorMapL2promotion)promo, CU_TENSOR_MAP_FLOAT_OOB_FILL_NONE);
}
void make_wmap(PFN_encodeTiled enc, CUtensorMap* m, const void* ptr, uint64_t cols, uint64_t rows, bool permuted) {
  cuuint64_t dims[5] = {cols, 2, 4, 4, rows / 32};
  cuuint64_t strides[4] = {cols * 2, cols * 2 * (permuted ? 8 : 2), cols * 2 * (permuted ? 2 : 8), cols * 2 * 32};
  cuuint32_t box[5] = {64, 2, 4, 4, 2};
  cuuint32_t es[5] = {1, 1, 1, 1, 1};
  enc(m, CU_TENSOR_MAP_DATA_TYPE_BFLOAT16, 5, const_cast<void*>(ptr), dims, strides, box, es, CU_TENSOR_MAP_INTERLEAVE_NONE,
      CU_TENSOR_MAP_SWIZZLE_128B, CU_TENSOR_MAP_L2_PROMOTION_L2_128B, CU_TENSOR_MAP_FLOAT_OOB_FILL_NONE);
}

}

extern "C" void kernel_launch(void* const* d_in, const int* in_sizes, int n_in, void* d_out, int out_size) {
  (void)in_sizes; (void)n_in; (void)out_size;
  static PFN_encodeTiled enc = nullptr;
  static void* scratch = nullptr;
  static int sms = 0;
  if (!enc) {
    int dev = 0;
    cudaGetDevice(&dev);
    cudaDeviceGetAttribute(&sms, cudaDevAttrMultiProcessorCount, dev);
    cudaGetSymbolAddress(&scratch, g_s);
    void* fn = nullptr;
    cudaDriverEntryPointQueryResult q;
    cudaGetDriverEntryPoint("cuTensorMapEncodeTiled", &fn, cudaEnableDefault, &q);
    enc = (PFN_encodeTiled)fn;
    cudaFuncSetAttribute(fused_kernel<true>, cudaFuncAttributeMaxDynamicSharedMemorySize, SMEM_BYTES);
    cudaFuncSetAttribute(fused_kernel<false>, cudaFuncAttributeMaxDynamicSharedMemorySize, SMEM_BYTES);
  }
  Params P;
  make_wmap(enc, &P.mWqkv, d_in[1], 3 * D_, D_, false);
  make_wmap(enc, &P.mWo, d_in[2], D_, D_, true);
  make_wmap(enc, &P.mWg, d_in[4], F_, D_, true);
  make_wmap(enc, &P.mWu, d_in[5], F_, D_, true);
  make_wmap(enc, &P.mWd, d_in[6], D_, F_, true);
  make_map(enc, &P.mOut, d_out, 2 * D_, S_ / 2, 16);
  make_map(enc, &P.mX, d_in[0], 2 * D_, S_ / 2, 64, CU_TENSOR_MAP_L2_PROMOTION_L2_128B);
  make_map(enc, &P.mWm2, d_in[8], 6 * D_, D_, 64, CU_TENSOR_MAP_L2_PROMOTION_L2_128B);
  Ptrs Q;
  Q.s = (Scratch*)scratch;
  Q.x = (const __nv_bfloat16*)d_in[0];
  Q.c = (const __nv_bfloat16*)d_in[7];
  Q.out = (__nv_bfloat16*)d_out;
  if (sms == NCTA + 4) fused_kernel<true><<<NCTA + 4, NTHREADS, SMEM_BYTES, cudaStreamPerThread>>>(Q, P);
  else fused_kernel<false><<<NCTA + 4, NTHREADS, SMEM_BYTES, cudaStreamPerThread>>>(Q, P);
}
```

```cpp
#include <cuda_runtime.h>
#include <cuda.h>
#include <cuda_bf16.h>
#include <stdint.h>
#include <stddef.h>
#include <string.h>
#include <math.h>

template <uint32_t HA, uint32_t HB> __device__ __forceinline__ void wg_n128(float (&d)[64], uint32_t descA, uint32_t descB, int scaleD) {
  asm volatile("{\n.reg .pred p;\n.reg .b64 da, db;\n"
    "mov.b64 da, {%64, %67};\nmov.b64 db, {%65, %68};\n"
    "setp.ne.b32 p, %66, 0;\n"
    "wgmma.mma_async.sync.aligned.m64n128k16.f32.bf16.bf16 "
    "{%0, %1, %2, %3, %4, %5, %6, %7, %8, %9, %10, %11, %12, %13, %14, %15, "
    "%16, %17, %18, %19, %20, %21, %22, %23, %24, %25, %26, %27, %28, %29, %30, %31, "
    "%32, %33, %34, %35, %36, %37, %38, %39, %40, %41, %42, %43, %44, %45, %46, %47, "
    "%48, %49, %50, %51, %52, %53, %54, %55, %56, %57, %58, %59, %60, %61, %62, %63}, "
    "da, db, p, 1, 1, 0, 1;\n}\n"
    : "+f"(d[0]), "+f"(d[1]), "+f"(d[2]), "+f"(d[3]), "+f"(d[4]), "+f"(d[5]), "+f"(d[6]), "+f"(d[7]),
      "+f"(d[8]), "+f"(d[9]), "+f"(d[10]), "+f"(d[11]), "+f"(d[12]), "+f"(d[13]), "+f"(d[14]), "+f"(d[15]),
      "+f"(d[16]), "+f"(d[17]), "+f"(d[18]), "+f"(d[19]), "+f"(d[20]), "+f"(d[21]), "+f"(d[22]), "+f"(d[23]),
      "+f"(d[24]), "+f"(d[25]), "+f"(d[26]), "+f"(d[27]), "+f"(d[28]), "+f"(d[29]), "+f"(d[30]), "+f"(d[31]),
      "+f"(d[32]), "+f"(d[33]), "+f"(d[34]), "+f"(d[35]), "+f"(d[36]), "+f"(d[37]), "+f"(d[38]), "+f"(d[39]),
      "+f"(d[40]), "+f"(d[41]), "+f"(d[42]), "+f"(d[43]), "+f"(d[44]), "+f"(d[45]), "+f"(d[46]), "+f"(d[47]),
      "+f"(d[48]), "+f"(d[49]), "+f"(d[50]), "+f"(d[51]), "+f"(d[52]), "+f"(d[53]), "+f"(d[54]), "+f"(d[55]),
      "+f"(d[56]), "+f"(d[57]), "+f"(d[58]), "+f"(d[59]), "+f"(d[60]), "+f"(d[61]), "+f"(d[62]), "+f"(d[63])
    : "r"(descA), "r"(descB), "r"(scaleD), "n"(HA), "n"(HB));
}
template <uint32_t HA, uint32_t HB> __device__ __forceinline__ void wg_n192(float (&d)[96], uint32_t descA, uint32_t descB, int scaleD) {
  asm volatile("{\n.reg .pred p;\n.reg .b64 da, db;\n"
    "mov.b64 da, {%96, %99};\nmov.b64 db, {%97, %100};\n"
    "setp.ne.b32 p, %98, 0;\n"
    "wgmma.mma_async.sync.aligned.m64n192k16.f32.bf16.bf16 "
    "{%0, %1, %2, %3, %4, %5, %6, %7, %8, %9, %10, %11, %12, %13, %14, %15, "
    "%16, %17, %18, %19, %20, %21, %22, %23, %24, %25, %26, %27, %28, %29, %30, %31, "
    "%32, %33, %34, %35, %36, %37, %38, %39, %40, %41, %42, %43, %44, %45, %46, %47, "
    "%48, %49, %50, %51, %52, %53, %54, %55, %56, %57, %58, %59, %60, %61, %62, %63, "
    "%64, %65, %66, %67, %68, %69, %70, %71, %72, %73, %74, %75, %76, %77, %78, %79, "
    "%80, %81, %82, %83, %84, %85, %86, %87, %88, %89, %90, %91, %92, %93, %94, %95}, "
    "da, db, p, 1, 1, 0, 1;\n}\n"
    : "+f"(d[0]), "+f"(d[1]), "+f"(d[2]), "+f"(d[3]), "+f"(d[4]), "+f"(d[5]), "+f"(d[6]), "+f"(d[7]),
      "+f"(d[8]), "+f"(d[9]), "+f"(d[10]), "+f"(d[11]), "+f"(d[12]), "+f"(d[13]), "+f"(d[14]), "+f"(d[15]),
      "+f"(d[16]), "+f"(d[17]), "+f"(d[18]), "+f"(d[19]), "+f"(d[20]), "+f"(d[21]), "+f"(d[22]), "+f"(d[23]),
      "+f"(d[24]), "+f"(d[25]), "+f"(d[26]), "+f"(d[27]), "+f"(d[28]), "+f"(d[29]), "+f"(d[30]), "+f"(d[31]),
      "+f"(d[32]), "+f"(d[33]), "+f"(d[34]), "+f"(d[35]), "+f"(d[36]), "+f"(d[37]), "+f"(d[38]), "+f"(d[39]),
      "+f"(d[40]), "+f"(d[41]), "+f"(d[42]), "+f"(d[43]), "+f"(d[44]), "+f"(d[45]), "+f"(d[46]), "+f"(d[47]),
      "+f"(d[48]), "+f"(d[49]), "+f"(d[50]), "+f"(d[51]), "+f"(d[52]), "+f"(d[53]), "+f"(d[54]), "+f"(d[55]),
      "+f"(d[56]), "+f"(d[57]), "+f"(d[58]), "+f"(d[59]), "+f"(d[60]), "+f"(d[61]), "+f"(d[62]), "+f"(d[63]),
      "+f"(d[64]), "+f"(d[65]), "+f"(d[66]), "+f"(d[67]), "+f"(d[68]), "+f"(d[69]), "+f"(d[70]), "+f"(d[71]),
      "+f"(d[72]), "+f"(d[73]), "+f"(d[74]), "+f"(d[75]), "+f"(d[76]), "+f"(d[77]), "+f"(d[78]), "+f"(d[79]),
      "+f"(d[80]), "+f"(d[81]), "+f"(d[82]), "+f"(d[83]), "+f"(d[84]), "+f"(d[85]), "+f"(d[86]), "+f"(d[87]),
      "+f"(d[88]), "+f"(d[89]), "+f"(d[90]), "+f"(d[91]), "+f"(d[92]), "+f"(d[93]), "+f"(d[94]), "+f"(d[95])
    : "r"(descA), "r"(descB), "r"(scaleD), "n"(HA), "n"(HB));
}
template <uint32_t HA, uint32_t HB> __device__ __forceinline__ void wg_n256(float (&d)[128], uint32_t descA, uint32_t descB, int scaleD) {
  asm volatile("{\n.reg .pred p;\n.reg .b64 da, db;\n"
    "mov.b64 da, {%128, %131};\nmov.b64 db, {%129, %132};\n"
    "setp.ne.b32 p, %130, 0;\n"
    "wgmma.mma_async.sync.aligned.m64n256k16.f32.bf16.bf16 "
    "{%0, %1, %2, %3, %4, %5, %6, %7, %8, %9, %10, %11, %12, %13, %14, %15, "
    "%16, %17, %18, %19, %20, %21, %22, %23, %24, %25, %26, %27, %28, %29, %30, %31, "
    "%32, %33, %34, %35, %36, %37, %38, %39, %40, %41, %42, %43, %44, %45, %46, %47, "
    "%48, %49, %50, %51, %52, %53, %54, %55, %56, %57, %58, %59, %60, %61, %62, %63, "
    "%64, %65, %66, %67, %68, %69, %70, %71, %72, %73, %74, %75, %76, %77, %78, %79, "
    "%80, %81, %82, %83, %84, %85, %86, %87, %88, %89, %90, %91, %92, %93, %94, %95, "
    "%96, %97, %98, %99, %100, %101, %102, %103, %104, %105, %106, %107, %108, %109, %110, %111, "
    "%112, %113, %114, %115, %116, %117, %118, %119, %120, %121, %122, %123, %124, %125, %126, %127}, "
    "da, db, p, 1, 1, 0, 1;\n}\n"
    : "+f"(d[0]), "+f"(d[1]), "+f"(d[2]), "+f"(d[3]), "+f"(d[4]), "+f"(d[5]), "+f"(d[6]), "+f"(d[7]),
      "+f"(d[8]), "+f"(d[9]), "+f"(d[10]), "+f"(d[11]), "+f"(d[12]), "+f"(d[13]), "+f"(d[14]), "+f"(d[15]),
      "+f"(d[16]), "+f"(d[17]), "+f"(d[18]), "+f"(d[19]), "+f"(d[20]), "+f"(d[21]), "+f"(d[22]), "+f"(d[23]),
      "+f"(d[24]), "+f"(d[25]), "+f"(d[26]), "+f"(d[27]), "+f"(d[28]), "+f"(d[29]), "+f"(d[30]), "+f"(d[31]),
      "+f"(d[32]), "+f"(d[33]), "+f"(d[34]), "+f"(d[35]), "+f"(d[36]), "+f"(d[37]), "+f"(d[38]), "+f"(d[39]),
      "+f"(d[40]), "+f"(d[41]), "+f"(d[42]), "+f"(d[43]), "+f"(d[44]), "+f"(d[45]), "+f"(d[46]), "+f"(d[47]),
      "+f"(d[48]), "+f"(d[49]), "+f"(d[50]), "+f"(d[51]), "+f"(d[52]), "+f"(d[53]), "+f"(d[54]), "+f"(d[55]),
      "+f"(d[56]), "+f"(d[57]), "+f"(d[58]), "+f"(d[59]), "+f"(d[60]), "+f"(d[61]), "+f"(d[62]), "+f"(d[63]),
      "+f"(d[64]), "+f"(d[65]), "+f"(d[66]), "+f"(d[67]), "+f"(d[68]), "+f"(d[69]), "+f"(d[70]), "+f"(d[71]),
      "+f"(d[72]), "+f"(d[73]), "+f"(d[74]), "+f"(d[75]), "+f"(d[76]), "+f"(d[77]), "+f"(d[78]), "+f"(d[79]),
      "+f"(d[80]), "+f"(d[81]), "+f"(d[82]), "+f"(d[83]), "+f"(d[84]), "+f"(d[85]), "+f"(d[86]), "+f"(d[87]),
      "+f"(d[88]), "+f"(d[89]), "+f"(d[90]), "+f"(d[91]), "+f"(d[92]), "+f"(d[93]), "+f"(d[94]), "+f"(d[95]),
      "+f"(d[96]), "+f"(d[97]), "+f"(d[98]), "+f"(d[99]), "+f"(d[100]), "+f"(d[101]), "+f"(d[102]), "+f"(d[103]),
      "+f"(d[104]), "+f"(d[105]), "+f"(d[106]), "+f"(d[107]), "+f"(d[108]), "+f"(d[109]), "+f"(d[110]), "+f"(d[111]),
      "+f"(d[112]), "+f"(d[113]), "+f"(d[114]), "+f"(d[115]), "+f"(d[116]), "+f"(d[117]), "+f"(d[118]), "+f"(d[119]),
      "+f"(d[120]), "+f"(d[121]), "+f"(d[122]), "+f"(d[123]), "+f"(d[124]), "+f"(d[125]), "+f"(d[126]), "+f"(d[127])
    : "r"(descA), "r"(descB), "r"(scaleD), "n"(HA), "n"(HB));
}

namespace {

constexpr int S_ = 2048, D_ = 1024, F_ = 3584;
constexpr int NCTA = 128;
constexpr int NTHREADS = 384;

constexpr uint32_t W_OFF      = 6 * 16384;
constexpr uint32_t BAR_OFF    = W_OFF + 16 * 8192;
constexpr uint32_t PAR_OFF    = BAR_OFF + 1280;
constexpr uint32_t SMEM_BYTES = 232448, SMEM_BASE = 1024;
constexpr uint32_t SL_OFF     = W_OFF + 11 * 8192;
constexpr uint32_t TAB_OFF    = W_OFF + 15 * 8192;
constexpr uint32_t B_R = 1024, B_PAR = 1072, B_SL = 1120, B_SLE = 1088, B_Q = 1096, B_ST = 1152, B_GB = 1056, B_XB = 1168, B_END = 1184, ROLE_OFF = 1272;

constexpr uint32_t H128 = 0x40000040u;
constexpr uint32_t H64  = 0x80000020u;

constexpr int N_W = 137, N_HK = 3, N_END = 130, N_PEEL = 3;
__constant__ uint2 c_cons[2][135] = {
  {
    {0x0,0x84580800}, {0x6000400,0x84580808}, {0x18000800,0x84580810}, {0x12000c00,0x84580818}, {0xc001000,0x84580820}, {0x0,0x84580828},
    {0x6000400,0x84580830}, {0x18000800,0x84580838}, {0x12000c00,0x84580840}, {0xc000000,0x84580848}, {0x800,0x84580850}, {0x6000c00,0x84580858},
    {0x18000000,0x84580860}, {0x12000800,0x84580868}, {0xc000c00,0x84580870}, {0x0,0x84580878}, {0x400,0x84580880}, {0x400,0x84580888},
    {0x18001000,0x4500890}, {0x1c000000,0x84580898}, {0x14000800,0x845818a0}, {0xc001400,0x41008a8}, {0x10000c00,0x845818b0}, {0x1000,0x41808b8},
    {0x4000000,0x845808c0}, {0x8000800,0x845808c8}, {0x1400,0x845808d0}, {0x1400,0x845808d8}, {0x18000000,0x3b808e0}, {0xc000800,0x845808e8},
    {0x12001400,0x845808f0}, {0xc00,0x845808f8}, {0x6001000,0x84580c00}, {0x18000400,0x84580c08}, {0xc000000,0x84580c10}, {0x12000800,0x84580c18},
    {0xc00,0x84580c20}, {0x6000400,0x84580c28}, {0x18000800,0x84580c30}, {0xc000c00,0x84580c38}, {0x12000400,0x84580c40}, {0x800,0x84580c48},
    {0x6000c00,0x84580c50}, {0x18000400,0x84580c58}, {0x0,0x3d80c60}, {0x14001400,0x83500c68}, {0xc00,0x84580c70}, {0x4001000,0x84580c78},
    {0x8000400,0x84580c80}, {0x18000000,0x84580c88}, {0xc000800,0x84580c90}, {0x10000c00,0x84580c98}, {0x1c000400,0x84580ca0}, {0x14000800,0x84580ca8},
    {0xc00,0x84580cb0}, {0x4000400,0x84580cb8}, {0x8000800,0x84580cc0}, {0x18000c00,0x84580cc8}, {0xc000400,0x84580cd0}, {0x10000800,0x84580cd8},
    {0x1c000c00,0x84580ce0}, {0x14001000,0x83d80ce8}, {0x400,0x84580cf0}, {0x4000000,0x84580cf8}, {0x8000800,0x84580800}, {0x18001400,0x84580808},
    {0xc000c00,0x84580810}, {0x10000400,0x84580818}, {0x1c000800,0x84580820}, {0x14000c00,0x84580828}, {0x400,0x84580830}, {0x4000800,0x84580838},
    {0x8000c00,0x84580840}, {0x18000400,0x84580848}, {0xc000800,0x84580850}, {0x10000c00,0x84580858}, {0x1c000400,0x84580860}, {0x14000000,0x3580868},
    {0x800,0x84580870}, {0x4001400,0x84580878}, {0x8000c00,0x84580880}, {0x18001000,0x84580888}, {0xc000400,0x84580890}, {0x10000000,0x84580898},
    {0x1c000800,0x845808a0}, {0x14001400,0x845808a8}, {0xc00,0x845808b0}, {0x4001000,0x845808b8}, {0x8000400,0x845808c0}, {0x18000000,0x845808c8},
    {0xc000800,0x845808d0}, {0x10001400,0x845808d8}, {0x1c000c00,0x845808e0}, {0x14001000,0x845808e8}, {0x400,0x845808f0}, {0x4000000,0x845808f8},
    {0x8000800,0x84580c00}, {0x18001400,0x84580c08}, {0xc000c00,0x84580c10}, {0x10001000,0x84580c18}, {0x1c000400,0x84580c20}, {0x14000000,0x84580c28},
    {0x800,0x84580c30}, {0x4001400,0x84580c38}, {0x8000c00,0x84580c40}, {0x18001000,0x84580c48}, {0xc000400,0x84580c50}, {0x10000000,0x84580c58},
    {0x1c000800,0x84580c60}, {0x14001400,0x84580c68}, {0xc00,0x84580c70}, {0x4001000,0x84580c78}, {0x8000400,0x84580c80}, {0x18000000,0x84580c88},
    {0xc000800,0x84580c90}, {0x10001400,0x84580c98}, {0x1c000c00,0x84580ca0}, {0x14001000,0x84580ca8}, {0x400,0x84580cb0}, {0x4000000,0x84580cb8},
    {0x8000800,0x84580cc0}, {0x18001400,0x84580cc8}, {0xc000c00,0x84580cd0}, {0x10001000,0x84580cd8}, {0x1c000400,0x84580ce0}, {0x14000000,0x84580ce8},
    {0x800,0x84580cf0}, {0x4001400,0x845804f8}, {0x8000c00,0x84580000}, {0x18001000,0x84580008}, {0x400,0x84580010}, {0x0,0x84580018},
    {0x14000800,0x0}, {0x14000800,0x0}, {0x14000800,0x0},
  },
  {
    {0x6001400,0x300900}, {0x18001000,0x380908}, {0x12000400,0x400910}, {0xc001400,0x480918}, {0x1000,0x500920}, {0x6000400,0x580928},
    {0x18001400,0x600930}, {0x12001000,0x680938}, {0xc000800,0x4480940}, {0x1400,0x84581948}, {0x6000c00,0x4001950}, {0x18001000,0x4080958},
    {0x12000000,0x84580960}, {0xc000800,0x84580968}, {0x1400,0x84580970}, {0x6000c00,0x84580978}, {0x400,0x84580980}, {0x400,0x84580988},
    {0x18000c00,0x2b80990}, {0x1c001000,0x84580998}, {0x14000400,0x845809a0}, {0xc000000,0x845809a8}, {0x10000800,0x845809b0}, {0x1400,0x845809b8},
    {0x4000c00,0xc009c0}, {0x8001000,0xc809c8}, {0x400,0x845809d0}, {0x400,0x845809d8}, {0xc001400,0x801009e0}, {0x12001000,0x801809e8},
    {0x0,0x802009f0}, {0x6001400,0x802809f8}, {0x18001000,0x80300d00}, {0xc000000,0x80380d08}, {0x12001400,0x80400d10}, {0x1000,0x80480d18},
    {0x6000000,0x82500d20}, {0x18000800,0x80580d28}, {0xc001400,0x84580d30}, {0x12000c00,0x84580d38}, {0x1000,0x84580d40}, {0x6000400,0x84580d48},
    {0x18000000,0x84580d50}, {0xc000800,0x84580d58}, {0x0,0x82600d60}, {0x14001400,0x82680d68}, {0x1000,0x82700d70}, {0x4000000,0x82780d78},
    {0x8001400,0x82800d80}, {0x18001000,0x82880d88}, {0xc000000,0x82900d90}, {0x10001400,0x82980d98}, {0x1c001000,0x82a00da0}, {0x14000000,0x82a80da8},
    {0x1400,0x82b00db0}, {0x4001000,0x82d80db8}, {0x8000400,0x84580dc0}, {0x18000000,0x84580dc8}, {0xc000800,0x84580dd0}, {0x10001400,0x84580dd8},
    {0x1c000c00,0x82e00de0}, {0x14001000,0x82e80de8}, {0x0,0x82f00df0}, {0x4001400,0x82f80df8}, {0x8001000,0x2000900}, {0x18000000,0x2080908},
    {0xc001400,0x2100910}, {0x10001000,0x2180918}, {0x1c000000,0x2200920}, {0x14001400,0x2280928}, {0x1000,0x2300930}, {0x4000000,0x2580938},
    {0x8000800,0x84580940}, {0x18001400,0x84580948}, {0xc000c00,0x84580950}, {0x10001000,0x84580958}, {0x1c000400,0x2600960}, {0x14000000,0x2680968},
    {0x800,0x2700970}, {0x4001400,0x2780978}, {0x8000c00,0x2800980}, {0x18001000,0x2880988}, {0xc000400,0x2900990}, {0x10000000,0x2980998},
    {0x1c000800,0x2a009a0}, {0x14001400,0x2a809a8}, {0xc00,0x2b009b0}, {0x4001000,0x2b809b8}, {0x8000400,0x2c009c0}, {0x18000000,0x2c809c8},
    {0xc000800,0x2d009d0}, {0x10001400,0x2d809d8}, {0x1c000c00,0x2e009e0}, {0x14001000,0x2e809e8}, {0x400,0x2f009f0}, {0x4000000,0x2f809f8},
    {0x8000800,0x82000d00}, {0x18001400,0x82080d08}, {0xc000c00,0x82100d10}, {0x10001000,0x82180d18}, {0x1c000400,0x82200d20}, {0x14000000,0x82280d28},
    {0x800,0x82300d30}, {0x4001400,0x82380d38}, {0x8000c00,0x82400d40}, {0x18001000,0x82480d48}, {0xc000400,0x82500d50}, {0x10000000,0x82580d58},
    {0x1c000800,0x82600d60}, {0x14001400,0x82680d68}, {0xc00,0x82700d70}, {0x4001000,0x82780d78}, {0x8000400,0x82800d80}, {0x18000000,0x82880d88},
    {0xc000800,0x82900d90}, {0x10001400,0x82980d98}, {0x1c000c00,0x82a00da0}, {0x14001000,0x82a80da8}, {0x400,0x82b00db0}, {0x4000000,0x82b80db8},
    {0x8000800,0x82c00dc0}, {0x18001400,0x82c80dc8}, {0xc000c00,0x82d00dd0}, {0x10001000,0x82d80dd8}, {0x1c000400,0x82e00de0}, {0x14000000,0x82e80de8},
    {0x800,0x82f005f0}, {0x4001400,0x80f805f8}, {0x8000c00,0x100}, {0x18001000,0x80108}, {0x400,0x84580110}, {0x0,0x84580118},
    {0x14000800,0x0}, {0x14000800,0x0}, {0x14000800,0x0},
  },
};
__constant__ uint2 c_act[2][135] = {
  {
    {0x81000458,0xa0000000}, {0x80004458,0xa0004008}, {0x80008458,0xa0008010}, {0x8000c458,0xa000c018}, {0x80010458,0xa0010020}, {0x14200,0xa0000028},
    {0x18208,0xa0004030}, {0x1c210,0xa0008038}, {0x3020218,0xa000c040}, {0x24228,0xa0000048}, {0x28238,0xa0008050}, {0x2c240,0xa000c058},
    {0x30248,0xa0000060}, {0x34250,0xa0008068}, {0x38258,0xa000c070}, {0x3c260,0xa0000078}, {0x328,0x4080}, {0x280,0x40004088},
    {0x5080358,0x80010090}, {0x88360,0x80000098}, {0x90368,0x800080a0}, {0x98370,0x800140a8}, {0xa0378,0x8000c0b0}, {0xa8290,0x800100b8},
    {0xb0298,0x800000c0}, {0xb82a0,0x800080c8}, {0x2a8,0x140d0}, {0x80000458,0x400140d8}, {0x70003a8,0xa00000e0}, {0x43b0,0xa00080e8},
    {0x83b8,0xa00140f0}, {0xc3c0,0xa000c0f8}, {0x103c8,0xa0010000}, {0x143d8,0xa0004008}, {0x182e0,0xa0000010}, {0x1c2e8,0xa0008018},
    {0x202f8,0xa000c020}, {0x80024208,0xa0004028}, {0x80028218,0xa0008030}, {0x8002c220,0xa000c038}, {0x80030228,0xa0004040}, {0x80034230,0xa0008048},
    {0x80038238,0xa000c050}, {0x8003c240,0xa0004058}, {0x80000458,0x20000060}, {0x80000330,0x80014068}, {0x80004338,0x8000c070}, {0x80008340,0x80010078},
    {0x8000c348,0x80004080}, {0x80010350,0x80000088}, {0x80014358,0x80008090}, {0x80018270,0x8000c098}, {0x8001c280,0x800040a0}, {0x80020290,0x800080a8},
    {0x80024298,0x8000c0b0}, {0x800282a0,0x800040b8}, {0x8002c2a8,0x800080c0}, {0x800302b0,0x8000c0c8}, {0x800342b8,0x800040d0}, {0x800382c0,0x800080d8},
    {0x8003c2c8,0x8000c0e0}, {0x800003b8,0x800100e8}, {0x800043c0,0x800040f0}, {0x800083c8,0x800000f8}, {0x8000c3d0,0x80008000}, {0x800103d8,0x80014008},
    {0x800143e0,0x8000c010}, {0x800182f0,0x80004018}, {0x1c200,0x80008020}, {0x20210,0x8000c028}, {0x24218,0x80004030}, {0x28220,0x80008038},
    {0x2c228,0x8000c040}, {0x30230,0x80004048}, {0x34238,0x80008050}, {0x38240,0x8000c058}, {0x3c248,0x80004060}, {0x918c338,0x60000068},
    {0x190340,0x60008070}, {0x194348,0x60014078}, {0x198350,0x6000c080}, {0x19c358,0x60010088}, {0x1a0360,0x60004090}, {0x1a4268,0x60000098},
    {0x1a8270,0x600080a0}, {0x1ac278,0x600140a8}, {0x1b0280,0x6000c0b0}, {0x1b4288,0x600100b8}, {0x1b8290,0x600040c0}, {0x1bc298,0x600000c8},
    {0x1c02a0,0x600080d0}, {0x1c42a8,0x600140d8}, {0x1c82b0,0x6000c0e0}, {0x1cc2b8,0x600100e8}, {0x1d02c0,0x600040f0}, {0x1d42c8,0x600000f8},
    {0x1d82d0,0x60008000}, {0x1dc2d8,0x60014008}, {0xb1e02e0,0x6000c010}, {0x1e42e8,0x60010018}, {0x1e82f0,0x60004020}, {0x1ec2f8,0x60000028},
    {0x801f0200,0x60008030}, {0x801f4208,0x60014038}, {0x801f8210,0x6000c040}, {0x801fc218,0x60010048}, {0x80200220,0x60004050}, {0x80204228,0x60000058},
    {0x80208230,0x60008060}, {0x8020c238,0x60014068}, {0x80210240,0x6000c070}, {0x80214248,0x60010078}, {0x80218250,0x60004080}, {0x8021c258,0x60000088},
    {0x8d220260,0x60008090}, {0x80224268,0x60014098}, {0x80228270,0x6000c0a0}, {0x8022c278,0x600100a8}, {0x80230280,0x600040b0}, {0x80234288,0x600000b8},
    {0x80238290,0x600080c0}, {0x8023c298,0x600140c8}, {0x802402a0,0x6000c0d0}, {0x802442a8,0x600100d8}, {0x802482b0,0x600040e0}, {0x8024c2b8,0x600000e8},
    {0x802502c0,0x600080f0}, {0x802542c8,0x600140f8}, {0x802582d0,0x6000c000}, {0x8025c2d8,0x60010008}, {0x801002e0,0x20004010}, {0x801042e8,0x20000018},
    {0x0,0x0}, {0x0,0x0}, {0x0,0x0},
  },
  {
    {0x91058458,0x40014100}, {0x5c220,0x40010108}, {0x60230,0x40004110}, {0x64300,0x40014118}, {0x68308,0x40010120}, {0x6c310,0x40004128},
    {0x70318,0x40014130}, {0x74320,0x40010138}, {0x78268,0x40008140}, {0x7c330,0x40014148}, {0x40270,0xa000c150}, {0x44338,0xa0010158},
    {0x48278,0xa0000160}, {0x4c340,0xa0008168}, {0x50348,0xa0014170}, {0x54350,0xa000c178}, {0x288,0x4180}, {0x380,0x40004188},
    {0x150c02b0,0x4000c190}, {0xc82b8,0x40010198}, {0xd0388,0x400041a0}, {0xd82c0,0x400001a8}, {0xe02c8,0x400081b0}, {0xe82d8,0x400141b8},
    {0xf0390,0x4000c1c0}, {0xf8398,0x400101c8}, {0x3a0,0x41d0}, {0x80000458,0x400041d8}, {0x170582f0,0x400141e0}, {0x8005c200,0x400101e8},
    {0x80060210,0x400001f0}, {0x643e0,0x400141f8}, {0x683e8,0x40010100}, {0x6c3f0,0x40000108}, {0x703f8,0x40014110}, {0x80074300,0x40010118},
    {0x80078308,0x40000120}, {0x8007c248,0x40008128}, {0x80040310,0xa0014130}, {0x80044250,0xa000c138}, {0x80048318,0xa0010140}, {0x8004c258,0xa0004148},
    {0x80050320,0xa0000150}, {0x80054328,0xa0008158}, {0x80000458,0x20000160}, {0x80040268,0x40014168}, {0x80044278,0x40010170}, {0x80048288,0x40000178},
    {0x8004c368,0x40014180}, {0x80050370,0x40010188}, {0x80054378,0x40000190}, {0x80058380,0x40014198}, {0x8005c388,0x400101a0}, {0x80060390,0x400001a8},
    {0x80064398,0x400141b0}, {0x800683a0,0x400101b8}, {0x8006c2d0,0x400041c0}, {0x800703a8,0x400001c8}, {0x800742d8,0x400081d0}, {0x800783b0,0x400141d8},
    {0x8007c2e0,0x4000c1e0}, {0x800402e8,0x400101e8}, {0x800442f8,0x400001f0}, {0x48208,0x400141f8}, {0x8004c3e8,0x40010100}, {0x800503f0,0x40000108},
    {0x800543f8,0x40014110}, {0x58300,0x40010118}, {0x5c308,0x40000120}, {0x60310,0x40014128}, {0x64318,0x40010130}, {0x68320,0x40000138},
    {0x6c250,0x40008140}, {0x70328,0x40014148}, {0x74258,0x4000c150}, {0x78330,0x40010158}, {0x7c260,0x40004160}, {0x918c338,0x20000168},
    {0x190340,0x20008170}, {0x194348,0x20014178}, {0x198350,0x2000c180}, {0x19c358,0x20010188}, {0x1a0360,0x20004190}, {0x1a4368,0x20000198},
    {0x1a8370,0x200081a0}, {0x1ac378,0x200141a8}, {0x1b0380,0x2000c1b0}, {0x1b4388,0x200101b8}, {0x1b8390,0x200041c0}, {0x1bc398,0x200001c8},
    {0x1c03a0,0x200081d0}, {0x1c43a8,0x200141d8}, {0x1c83b0,0x2000c1e0}, {0x1cc3b8,0x200101e8}, {0x1d03c0,0x200041f0}, {0x1d43c8,0x200001f8},
    {0x1d83d0,0x20008100}, {0x1dc3d8,0x20014108}, {0xb1e03e0,0x2000c110}, {0x1e43e8,0x20010118}, {0x1e83f0,0x20004120}, {0x1ec3f8,0x20000128},
    {0x801f0300,0x20008130}, {0x801f4308,0x20014138}, {0x801f8310,0x2000c140}, {0x801fc318,0x20010148}, {0x80200320,0x20004150}, {0x80204328,0x20000158},
    {0x80208330,0x20008160}, {0x8020c338,0x20014168}, {0x80210340,0x2000c170}, {0x80214348,0x20010178}, {0x80218350,0x20004180}, {0x8021c358,0x20000188},
    {0x8d220360,0x20008190}, {0x80224368,0x20014198}, {0x80228370,0x2000c1a0}, {0x8022c378,0x200101a8}, {0x80230380,0x200041b0}, {0x80234388,0x200001b8},
    {0x80238390,0x200081c0}, {0x8023c398,0x200141c8}, {0x802403a0,0x2000c1d0}, {0x802443a8,0x200101d8}, {0x802483b0,0x200041e0}, {0x8024c3b8,0x200001e8},
    {0x802503c0,0x200081f0}, {0x802543c8,0x200141f8}, {0x802583d0,0x2000c100}, {0x8025c3d8,0x20010108}, {0x801003e0,0x20004110}, {0x801043e8,0x20000118},
    {0x0,0x0}, {0x0,0x0}, {0x0,0x0},
  },
};
__constant__ uint2 c_w[1][138] = {
  {
    {0x84580000,0x20000}, {0x84580000,0x2026008}, {0x84580000,0x4038010}, {0x84580000,0x6032018}, {0x84580000,0x802c020}, {0x2000000,0xa000028},
    {0x2080000,0xc006030}, {0x2100000,0xe018038}, {0x2180000,0x10012040}, {0x2200000,0x1200c048}, {0x2280000,0x14000050}, {0x2300300,0x16006058},
    {0x2380308,0x18018060}, {0x2400310,0x1a012068}, {0x2480318,0x1c00c070}, {0x2500320,0x1e000078}, {0x2580328,0x6150}, {0x2600330,0x2018158},
    {0x2680338,0x4012160}, {0x2700340,0x600c168}, {0x2780348,0x8000170}, {0x3500000,0xa026178}, {0x3580000,0x18890}, {0x84580000,0x401c898},
    {0x3600000,0x80148a0}, {0x3680000,0xc00c8a8}, {0x84580000,0x100108b0}, {0x3700000,0x140008b8}, {0x3780000,0x180048c0}, {0x84580000,0x1c0288c8},
    {0x3980000,0x184e0}, {0x3b00000,0x200c4e8}, {0x84580000,0x40124f0}, {0x2c003c0,0x60004f8}, {0x2c803c8,0x8006400}, {0x2e00000,0xa018408},
    {0x2e80000,0xc00c410}, {0x2f00000,0xe012418}, {0x2f80000,0x10000420}, {0x82000000,0x12006428}, {0x82080000,0x14018430}, {0x821003e0,0x1600c438},
    {0x821803e8,0x18012440}, {0x822003f0,0x1a000448}, {0x822803f8,0x1c006450}, {0x82308300,0x1e018458}, {0x82388308,0xc530}, {0x82408310,0x2012538},
    {0x82488318,0x4000540}, {0x83200000,0x6006548}, {0x82588328,0x8018550}, {0x83300000,0xa02c558}, {0x83380000,0x14c68}, {0x83400000,0x2000c70},
    {0x83480000,0x4004c78}, {0x84580000,0x6008c80}, {0x83500000,0x8018c88}, {0x83580000,0xa00cc90}, {0x84580000,0xc010c98}, {0x83600000,0xe01cca0},
    {0x83680000,0x10014ca8}, {0x83700000,0x12000cb0}, {0x83780000,0x14004cb8}, {0x83800000,0x16008cc0}, {0x83880000,0x18018cc8}, {0x83900000,0x1a00ccd0},
    {0x83980000,0x1c010cd8}, {0x83a00000,0x1e03cce0}, {0x83a80000,0x150e8}, {0x83b00000,0x20010f0}, {0x83b80000,0x40050f8}, {0x83c00000,0x6009000},
    {0x83c80000,0x8019008}, {0x83d00000,0xa00d010}, {0x83d80000,0xc011018}, {0x83e00000,0xe01d020}, {0x83e80000,0x10015028}, {0x83f00000,0x12001030},
    {0x83f80000,0x14005038}, {0x3000000,0x16009040}, {0x3080000,0x18019048}, {0x3100000,0x1a00d050}, {0x3180000,0x1c011058}, {0x3200000,0x1e03d060},
    {0x3280000,0x6015468}, {0x3300000,0x8001470}, {0x3380000,0xa005478}, {0x3400000,0xc009480}, {0x3480000,0xe019488}, {0x3500000,0x1000d490},
    {0x3580000,0x12011498}, {0x3600000,0x1401d4a0}, {0x3680000,0x160154a8}, {0x3700000,0x180014b0}, {0x3780000,0x1a0054b8}, {0x3800000,0x1c0094c0},
    {0x3880000,0x1e0194c8}, {0x3900000,0x2000d4d0}, {0x3980000,0x220114d8}, {0x3a00000,0x2401d4e0}, {0x3a80000,0x260154e8}, {0x3b00000,0x280014f0},
    {0x3b80000,0x2a0054f8}, {0x3c00000,0x2c009400}, {0x3c80000,0x2e019408}, {0x3d00000,0x3000d410}, {0x3d80000,0x32011418}, {0x3e00000,0x3401d420},
    {0x3e80000,0x36015428}, {0x3f00000,0x38001430}, {0x3f80000,0x3a005438}, {0x83000000,0x3c009440}, {0x83080000,0x3e019448}, {0x83100000,0x4000d450},
    {0x83180000,0x42011458}, {0x83200000,0x4401d460}, {0x83280000,0x46015468}, {0x83300000,0x48001470}, {0x83380000,0x4a005478}, {0x83400000,0x4c009480},
    {0x83480000,0x4e019488}, {0x83500000,0x5000d490}, {0x83580000,0x52011498}, {0x83600000,0x5401d4a0}, {0x83680000,0x560154a8}, {0x83700000,0x580014b0},
    {0x83780000,0x5a0054b8}, {0x83800000,0x5c0094c0}, {0x83880000,0x5e0194c8}, {0x83900000,0x6000d4d0}, {0x83980000,0x620114d8}, {0x83a00000,0x6401d4e0},
    {0x83a80000,0x660154e8}, {0x83b00000,0x680014f0}, {0x83b80000,0x6a0054f8}, {0x83c00000,0x6c009400}, {0x83c80000,0x6e039408}, {0x0,0x0},
  },
};

constexpr int T_H = 0, T_O = 32, T_X1 = 64, T_ACT = 96, N_TILES = 208;
constexpr int G_H0 = 0, G_H1 = 1, G_O = 2, G_H2 = 3, G_ACT = 4, G_X1 = 7, G_HK = 15;

struct Scratch {
  uint4 img[8 * N_TILES * 1024];
  uint32_t mod0[4 * 4 * 512];
  uint32_t modp[4096];
  uint2 stat[32 * 8 * 64];
  uint4 halo[16 * 16 * 128];
  uint32_t cnt[8 * 32];
  uint32_t ep[(NCTA + 4) * 32];
};
__device__ __align__(1024) Scratch g_s;

struct Ptrs {
  const __nv_bfloat16 *x, *c;
  Scratch* s;
  __nv_bfloat16* out;
};
struct Params {
  CUtensorMap mWqkv, mWo, mWg, mWu, mWd, mOut, mWm2, mX;
};

__device__ __forceinline__ uint32_t smem_u32(const void* p) { return (uint32_t)__cvta_generic_to_shared(p); }
__device__ __forceinline__ void mbar_init(uint32_t bar, uint32_t cnt) { asm volatile("mbarrier.init.shared::cta.b64 [%0], %1;" ::"r"(bar), "r"(cnt)); }
__device__ __forceinline__ void mbar_expect_tx(uint32_t bar, uint32_t bytes) { asm volatile("mbarrier.arrive.expect_tx.shared::cta.b64 _, [%0], %1;" ::"r"(bar), "r"(bytes) : "memory"); }
__device__ __forceinline__ void mbar_arrive(uint32_t bar) { asm volatile("mbarrier.arrive.shared::cta.b64 _, [%0];" ::"r"(bar) : "memory"); }
__device__ __forceinline__ void mbar_arrive_remote(uint32_t bar_cluster) { asm volatile("mbarrier.arrive.shared::cluster.b64 _, [%0];" ::"r"(bar_cluster) : "memory"); }
__device__ __forceinline__ uint32_t mapa(uint32_t a, uint32_t cta) { uint32_t r; asm volatile("mapa.shared::cluster.u32 %0, %1, %2;" : "=r"(r) : "r"(a), "r"(cta)); return r; }
__device__ __forceinline__ void mbar_wait(uint32_t bar, uint32_t parity) {
  asm volatile("{\n.reg .pred p;\nW: mbarrier.try_wait.parity.shared::cta.b64 p, [%0], %1;\n@!p bra W;\n}" ::"r"(bar), "r"(parity) : "memory");
}
__device__ __forceinline__ void mbar_wait_bounded(uint32_t bar, uint32_t parity) {
  asm volatile("{\n.reg .pred p;\n.reg .u32 c;\nmov.u32 c, 0;\n"
               "W: mbarrier.try_wait.parity.shared::cta.b64 p, [%0], %1;\n@p bra D;\n"
               "add.u32 c, c, 1;\nsetp.lt.u32 p, c, 0x200000;\n@p bra W;\ntrap;\nD:\n}" ::"r"(bar), "r"(parity) : "memory");
}
constexpr uint32_t POLL_MAX = 1u << 20;
__device__ __forceinline__ void guard(uint32_t it) { asm volatile("{\n.reg .pred p;\nsetp.gt.u32 p, %0, 0x100000;\n@p trap;\n}" ::"r"(it)); }
__device__ __forceinline__ bool mbar_test(uint32_t bar, uint32_t parity) {
  uint32_t p; asm volatile("{\n.reg .pred P;\nmbarrier.test_wait.parity.shared::cta.b64 P, [%1], %2;\nselp.u32 %0, 1, 0, P;\n}" : "=r"(p) : "r"(bar), "r"(parity) : "memory"); return p;
}
__device__ __forceinline__ bool elect_one() {
  uint32_t p; asm volatile("{\n.reg .pred P;\nelect.sync _|P, 0xffffffff;\nselp.u32 %0, 1, 0, P;\n}" : "=r"(p)); return p;
}
__device__ __forceinline__ bool only_one() { asm volatile("{\n.reg .pred P;\nelect.sync _|P, 0xffffffff;\n@!P exit;\n}" ::: "memory"); return true; }
__device__ __forceinline__ void tma2d(uint32_t dst, const CUtensorMap* m, uint32_t bar, int c0, int c1) {
  asm volatile("cp.async.bulk.tensor.2d.shared::cluster.global.mbarrier::complete_tx::bytes [%0], [%1, {%3, %4}], [%2];" ::"r"(dst), "l"(m), "r"(bar), "r"(c0), "r"(c1) : "memory");
}
__device__ __forceinline__ uint64_t evict_first() { uint64_t p; asm("createpolicy.fractional.L2::evict_first.b64 %0, 1.0;" : "=l"(p)); return p; }
__device__ __forceinline__ void tma2d_once(uint32_t dst, const CUtensorMap* m, uint32_t bar, int c0, int c1) {
  asm volatile("cp.async.bulk.tensor.2d.shared::cluster.global.mbarrier::complete_tx::bytes.L2::cache_hint [%0], [%1, {%3, %4}], [%2], %5;" ::"r"(dst), "l"(m), "r"(bar), "r"(c0), "r"(c1), "l"(evict_first()) : "memory");
}
__device__ __forceinline__ void tma5d_once(uint32_t dst, const CUtensorMap* m, uint32_t bar, int c0, int c4) {
  asm volatile("cp.async.bulk.tensor.5d.shared::cluster.global.mbarrier::complete_tx::bytes.L2::cache_hint [%0], [%1, {%3, %5, %5, %5, %4}], [%2], %6;" ::"r"(dst), "l"(m), "r"(bar), "r"(c0), "r"(c4), "r"(0), "l"(evict_first()) : "memory");
}
__device__ __forceinline__ void tma5d(uint32_t dst, const CUtensorMap* m, uint32_t bar, int c0, int c4) {
  asm volatile("cp.async.bulk.tensor.5d.shared::cluster.global.mbarrier::complete_tx::bytes [%0], [%1, {%3, %5, %5, %5, %4}], [%2];" ::"r"(dst), "l"(m), "r"(bar), "r"(c0), "r"(c4), "r"(0) : "memory");
}
__device__ __forceinline__ void tma2d_st(const CUtensorMap* m, uint32_t src, int c0, int c1) {
  asm volatile("cp.async.bulk.tensor.2d.global.shared::cta.bulk_group [%0, {%2, %3}], [%1];" ::"l"(m), "r"(src), "r"(c0), "r"(c1) : "memory");
}
__device__ __forceinline__ void bulk_g2s(uint32_t dst, const void* src, uint32_t bytes, uint32_t bar) {
  asm volatile("cp.async.bulk.shared::cluster.global.mbarrier::complete_tx::bytes [%0], [%1], %2, [%3];" ::"r"(dst), "l"(src), "r"(bytes), "r"(bar) : "memory");
}
__device__ __forceinline__ void bulk_g2s_mc(uint32_t dst, const void* src, uint32_t bytes, uint32_t bar) {
  asm volatile("cp.async.bulk.shared::cluster.global.mbarrier::complete_tx::bytes.multicast::cluster [%0], [%1], %2, [%3], %4;" ::"r"(dst), "l"(src), "r"(bytes), "r"(bar), "h"((uint16_t)3) : "memory");
}
__device__ __forceinline__ void st_async(uint32_t dst, uint32_t bar, uint32_t a, uint32_t b, uint32_t c, uint32_t d) {
  asm volatile("st.async.weak.shared::cluster.mbarrier::complete_tx::bytes.v4.b32 [%0], {%2,%3,%4,%5}, [%1];" ::"r"(dst), "r"(bar), "r"(a), "r"(b), "r"(c), "r"(d) : "memory");
}
__device__ __forceinline__ void bulk_commit() { asm volatile("cp.async.bulk.commit_group;" ::: "memory"); }
__device__ __forceinline__ void bulk_wait_read() { asm volatile("cp.async.bulk.wait_group.read 0;" ::: "memory"); }
__device__ __forceinline__ void fence_async_smem() { asm volatile("fence.proxy.async.shared::cta;" ::: "memory"); }
__device__ __forceinline__ void fence_async_glob() { asm volatile("fence.proxy.async.global;" ::: "memory"); }
__device__ __forceinline__ void prefetch_tmap(const CUtensorMap* m) { asm volatile("prefetch.tensormap [%0];" ::"l"(m) : "memory"); }
__device__ __forceinline__ void wg_fence() { asm volatile("wgmma.fence.sync.aligned;" ::: "memory"); }
__device__ __forceinline__ void wg_commit() { asm volatile("wgmma.commit_group.sync.aligned;" ::: "memory"); }
template <int N> __device__ __forceinline__ void wg_wait() { asm volatile("wgmma.wait_group.sync.aligned %0;" ::"n"(N) : "memory"); }
template <int N> __device__ __forceinline__ void fence_regs(float (&a)[N]) {
#pragma unroll
  for (int i = 0; i < N; i++) asm volatile("" : "+f"(a[i])::"memory");
}
__device__ __forceinline__ uint32_t make_desc(uint32_t addr, uint32_t lbo) { return ((addr & 0x3FFFF) >> 4) | ((lbo >> 4) << 16); }
__device__ __forceinline__ void named_sync(int id, int n) { asm volatile("bar.sync %0, %1;" ::"r"(id), "r"(n) : "memory"); }
__device__ __forceinline__ uint32_t ld_relaxed(const void* p) { uint32_t v; asm volatile("ld.relaxed.gpu.global.u32 %0, [%1];" : "=r"(v) : "l"(p) : "memory"); return v; }
__device__ __forceinline__ uint32_t ld_relaxed_line(const void* p) { uint32_t v; asm volatile("ld.relaxed.gpu.global.L2::128B.u32 %0, [%1];" : "=r"(v) : "l"(p) : "memory"); return v; }
__device__ __forceinline__ void red_relaxed(uint32_t* p, uint32_t v) { asm volatile("red.relaxed.gpu.global.add.u32 [%0], %1;" ::"l"(p), "r"(v) : "memory"); }
__device__ __forceinline__ void st_relaxed(uint32_t* p, uint32_t v) { asm volatile("st.relaxed.gpu.global.u32 [%0], %1;" ::"l"(p), "r"(v) : "memory"); }
__device__ __forceinline__ uint2 ld_relaxed_b64(const uint2* p) {
  uint64_t a; asm volatile("ld.relaxed.gpu.global.b64 %0, [%1];" : "=l"(a) : "l"(p) : "memory");
  return make_uint2((uint32_t)a, (uint32_t)(a >> 32));
}
__device__ __forceinline__ void st_relaxed_b64(void* p, uint32_t lo, uint32_t hi) {
  uint64_t v = ((uint64_t)hi << 32) | lo;
  asm volatile("st.relaxed.gpu.global.b64 [%0], %1;" ::"l"(p), "l"(v) : "memory");
}
__device__ __forceinline__ void st_relaxed_v4(uint4* p, uint32_t a, uint32_t b, uint32_t c, uint32_t d) {
  asm volatile("st.relaxed.gpu.global.v4.u32 [%0], {%1,%2,%3,%4};" ::"l"(p), "r"(a), "r"(b), "r"(c), "r"(d) : "memory");
}
__device__ __forceinline__ bool empty(const uint4& v) { return v.x == ~0u || v.y == ~0u || v.z == ~0u || v.w == ~0u; }
__device__ __forceinline__ uint32_t tag_of(uint32_t ep) { return ep % 3 + 1; }
__device__ __forceinline__ uint32_t tagf(float v, uint32_t ep) {
  uint32_t r; asm volatile("lop3.b32 %0, %1, %2, 3, 0xD8;" : "=r"(r) : "r"(__float_as_uint(v)), "r"(ep)); return r;
}
__device__ __forceinline__ uint32_t tag_bad(const uint4& v, uint32_t ep) { return ((v.x ^ ep) | (v.y ^ ep) | (v.z ^ ep) | (v.w ^ ep)) & 3u; }
__device__ __forceinline__ uint4 ld_relaxed_v4(const void* p) {
  uint4 v; asm volatile("ld.relaxed.gpu.global.v4.u32 {%0,%1,%2,%3}, [%4];" : "=r"(v.x), "=r"(v.y), "=r"(v.z), "=r"(v.w) : "l"(p) : "memory"); return v;
}
__device__ __forceinline__ uint32_t ldg32(const void* p) { uint32_t v; asm volatile("ld.global.u32 %0, [%1];" : "=r"(v) : "l"(p) : "memory"); return v; }
__device__ __forceinline__ void stg128(uint4* p, uint32_t a, uint32_t b, uint32_t c, uint32_t d) {
  asm volatile("st.global.v4.b32 [%0], {%1,%2,%3,%4};" ::"l"(p), "r"(a), "r"(b), "r"(c), "r"(d) : "memory");
}
__device__ __forceinline__ void landed(uint32_t v) { if (__all_sync(~0u, v == 0xffffffffu)) __nanosleep(1); }
__device__ __forceinline__ void publish(uint32_t seen, uint32_t* cnt, uint32_t inc) {
  landed(seen);
  if (elect_one()) red_relaxed(cnt, inc);
}
__device__ __forceinline__ uint32_t pack_bf16(float lo, float hi) { uint32_t r; asm("cvt.rn.bf16x2.f32 %0, %1, %2;" : "=r"(r) : "f"(hi), "f"(lo)); return r; }
__device__ __forceinline__ float bf_lo(uint32_t v) { return __uint_as_float(v << 16); }
__device__ __forceinline__ float bf_hi(uint32_t v) { return __uint_as_float(v & 0xffff0000u); }
__device__ __forceinline__ uint32_t hmul2_bf16(uint32_t a, uint32_t b) { uint32_t r; asm("mul.rn.bf16x2 %0, %1, %2;" : "=r"(r) : "r"(a), "r"(b)); return r; }
__device__ __forceinline__ uint32_t hadd2_bf16(uint32_t a, uint32_t b) { uint32_t r; asm("add.rn.bf16x2 %0, %1, %2;" : "=r"(r) : "r"(a), "r"(b)); return r; }
__device__ __forceinline__ uint32_t hfma2_bf16(uint32_t a, uint32_t b, uint32_t c) { uint32_t r; asm("fma.rn.bf16x2 %0, %1, %2, %3;" : "=r"(r) : "r"(a), "r"(b), "r"(c)); return r; }
__device__ __forceinline__ void wgmma_n8(float (&d)[4], uint32_t descA, uint32_t descB, int scaleD) {
  asm volatile("{\n.reg .pred p;\n.reg .b64 da, db;\nmov.b64 da, {%4, 0x40000040};\nmov.b64 db, {%5, 0x40000040};\nsetp.ne.b32 p, %6, 0;\n"
               "wgmma.mma_async.sync.aligned.m64n8k16.f32.bf16.bf16 {%0,%1,%2,%3}, da, db, p, 1, 1, 1, 0;\n}\n"
               : "+f"(d[0]), "+f"(d[1]), "+f"(d[2]), "+f"(d[3]) : "r"(descA), "r"(descB), "r"(scaleD));
}
__device__ __forceinline__ float ex2(float x) { float r; asm("ex2.approx.ftz.f32 %0, %1;" : "=f"(r) : "f"(x)); return r; }
__device__ __forceinline__ float rcp(float x) { float r; asm("rcp.approx.ftz.f32 %0, %1;" : "=f"(r) : "f"(x)); return r; }
__device__ __forceinline__ float silu_f(float x) { return x * rcp(1.f + ex2(x * -1.4426950408889634f)); }
__device__ __forceinline__ float swiglu(float h, float hu) {
  float t; asm("tanh.approx.f32 %0, %1;" : "=f"(t) : "f"(h));
  return fmaf(hu, t, hu);
}
__device__ __forceinline__ void ldsm4(uint32_t addr, uint32_t& a, uint32_t& b, uint32_t& c, uint32_t& d) {
  asm volatile("ldmatrix.sync.aligned.m8n8.x4.shared.b16 {%0,%1,%2,%3}, [%4];" : "=r"(a), "=r"(b), "=r"(c), "=r"(d) : "r"(addr) : "memory");
}
__device__ __forceinline__ void stsm4(uint32_t addr, uint32_t a, uint32_t b, uint32_t c, uint32_t d) {
  asm volatile("stmatrix.sync.aligned.m8n8.x4.shared.b16 [%0], {%1,%2,%3,%4};" ::"r"(addr), "r"(a), "r"(b), "r"(c), "r"(d) : "memory");
}
__device__ __forceinline__ void sts128(uint32_t addr, uint32_t a, uint32_t b, uint32_t c, uint32_t d) {
  asm volatile("st.shared.v4.b32 [%0], {%1,%2,%3,%4};" ::"r"(addr), "r"(a), "r"(b), "r"(c), "r"(d) : "memory");
}
__device__ __forceinline__ void sts64(uint32_t addr, uint32_t a, uint32_t b) { asm volatile("st.shared.v2.b32 [%0], {%1,%2};" ::"r"(addr), "r"(a), "r"(b) : "memory"); }
__device__ __forceinline__ void sts32(uint32_t addr, uint32_t a) { asm volatile("st.shared.b32 [%0], %1;" ::"r"(addr), "r"(a) : "memory"); }
__device__ __forceinline__ uint4 lds128(uint32_t addr) {
  uint4 v; asm volatile("ld.shared.v4.b32 {%0,%1,%2,%3}, [%4];" : "=r"(v.x), "=r"(v.y), "=r"(v.z), "=r"(v.w) : "r"(addr) : "memory"); return v;
}
__device__ __forceinline__ uint32_t lds32(uint32_t addr) { uint32_t v; asm volatile("ld.shared.b32 %0, [%1];" : "=r"(v) : "r"(addr) : "memory"); return v; }
__device__ __forceinline__ uint32_t movm(uint32_t a) { uint32_t d; asm volatile("movmatrix.sync.aligned.m8n8.trans.b16 %0, %1;" : "=r"(d) : "r"(a)); return d; }
__device__ __forceinline__ void mma16816(float (&c)[4], uint32_t a0, uint32_t a1, uint32_t a2, uint32_t a3, uint32_t b0, uint32_t b1) {
  asm volatile("mma.sync.aligned.m16n8k16.row.col.f32.bf16.bf16.f32 {%0,%1,%2,%3},{%4,%5,%6,%7},{%8,%9},{%0,%1,%2,%3};"
               : "+f"(c[0]), "+f"(c[1]), "+f"(c[2]), "+f"(c[3]) : "r"(a0), "r"(a1), "r"(a2), "r"(a3), "r"(b0), "r"(b1));
}
__device__ __forceinline__ void mma16816z(float (&c)[4], uint32_t a0, uint32_t a1, uint32_t a2, uint32_t a3, uint32_t b0, uint32_t b1) {
  asm volatile("mma.sync.aligned.m16n8k16.row.col.f32.bf16.bf16.f32 {%0,%1,%2,%3},{%4,%5,%6,%7},{%8,%9},{%10,%10,%10,%10};"
               : "=f"(c[0]), "=f"(c[1]), "=f"(c[2]), "=f"(c[3]) : "r"(a0), "r"(a1), "r"(a2), "r"(a3), "r"(b0), "r"(b1), "f"(0.f));
}
__device__ __forceinline__ void mma1688(float (&c)[4], uint32_t a0, uint32_t a1, uint32_t b0) {
  asm volatile("mma.sync.aligned.m16n8k8.row.col.f32.bf16.bf16.f32 {%0,%1,%2,%3},{%4,%5},{%6},{%0,%1,%2,%3};"
               : "+f"(c[0]), "+f"(c[1]), "+f"(c[2]), "+f"(c[3]) : "r"(a0), "r"(a1), "r"(b0));
}
__device__ __forceinline__ float quad_max(float v) { v = fmaxf(v, __shfl_xor_sync(~0u, v, 1)); return fmaxf(v, __shfl_xor_sync(~0u, v, 2)); }
__device__ __forceinline__ float quad_sum(float v) { v += __shfl_xor_sync(~0u, v, 1); return v + __shfl_xor_sync(~0u, v, 2); }
__device__ __forceinline__ uint32_t opaque(uint32_t v) { asm volatile("" : "+r"(v)); return v; }
__device__ __forceinline__ uint32_t tid_now() { uint32_t v; asm volatile("mov.u32 %0, %%tid.x;" : "=r"(v)); return v; }
__device__ __forceinline__ void arrive_after(uint32_t bar, float v) {
  asm volatile("{\n.reg .pred p, q;\n.reg .b32 c;\nmov.b32 c, %1;\nelect.sync _|q, 0xffffffff;\n"
               "L: @q mbarrier.arrive.shared::cta.b64 _, [%0];\nsetp.eq.u32 p, c, 0x7fedcba9;\nadd.u32 c, c, 1;\nsetp.ne.u32 q, c, c;\n@p bra L;\n}"
               ::"r"(bar), "r"(__float_as_uint(v)) : "memory");
}
__device__ __forceinline__ int since(int t0) { return (int)((uint32_t)clock() - (uint32_t)t0); }
__device__ __forceinline__ void until(int t0, uint32_t t) { while ((uint32_t)since(t0) < t) {} }
__device__ __forceinline__ void in_order() { const int t = (int)clock(); while (since(t) < 0) {} }
__device__ __forceinline__ void spin(int clocks) { until((int)clock(), clocks); }

constexpr float ATT_SCALE_LOG2E = 0.17677669529663687f * 1.4426950408889634f;

constexpr int T_XA = 2600;
constexpr int P_XB = 100;
constexpr int P_ACT = 140;
constexpr int T_Q2 = 3750;
constexpr int T_Q3 = 4150;
constexpr int T_XB = 8050;
constexpr int DELAY_ST = 150;
constexpr int T_W0 = 3200;
constexpr int T_G0 = 4500;
constexpr int T_G1 = 7250;
constexpr int P_G2 = 690;
constexpr int P_G2B = 820;
constexpr int F_G2A = 700;
constexpr int F_G2B = 750;
constexpr int P_Q = 240;
constexpr int T_W = 5500;
constexpr int P_W = 1200;
constexpr int DELAY_HELP = 3000;

struct Pipe {
  const uint2* tab;
  uint32_t bars, peer_bars;
  uint2 nx;
  uint32_t prev;
  bool ready;
  bool lead;
  __device__ __forceinline__ uint2 begin(int n) {
    const uint2 e = nx;
    nx = tab[n + 1];
    if (!ready) {
      mbar_wait(bars + (e.y & 0x3ff), (e.y >> 10) & 1);
      mbar_wait(bars + ((e.y >> 16) & 0x7ff), e.y >> 31);
    }
    ready = false;
    return e;
  }
  __device__ __forceinline__ void release_now(uint32_t y) {
    asm volatile("{\n.reg .pred p, q;\n.reg .b32 c;\nmov.b32 c, %2;\nelect.sync _|q, 0xffffffff;\nsetp.ne.and.u32 q, c, 0, q;\n"
                 "L: @q mbarrier.arrive.shared::cta.b64 _, [%0];\n@q mbarrier.arrive.shared::cluster.b64 _, [%1];\n"
                 "setp.eq.u32 p, c, 1;\nadd.u32 c, c, 1;\n@p bra L;\n}"
                 ::"r"(bars + 512 + (y & 0x3ff)), "r"(peer_bars + 512 + (y & 0x3ff)), "r"(opaque(lead ? y & 0x800 : 0)) : "memory");
  }
  template <bool PAUSES = false> __device__ __forceinline__ void end(uint32_t y) {
    const bool r0 = mbar_test(bars + (nx.y & 0x3ff), (nx.y >> 10) & 1), r1 = mbar_test(bars + ((nx.y >> 16) & 0x7ff), nx.y >> 31);
    wg_wait<1>();
    release(prev);
    prev = y;
    if (PAUSES && (y & 0x1000)) { wg_wait<0>(); release(y); prev = 0; }
    ready = __all_sync(~0u, r0 && r1);
  }
  __device__ __forceinline__ void release(uint32_t y) {
    if (lead && (y & 0x800)) { if (elect_one()) { mbar_arrive(bars + 512 + (y & 0x3ff)); mbar_arrive_remote(peer_bars + 512 + (y & 0x3ff)); } }
  }
};
__device__ __forceinline__ constexpr uint32_t qa(int q) { return (q >> 1) * 256 + (q & 1) * 2; }

__device__ __forceinline__ uint32_t img_pos(uint32_t w, uint32_t lane) { return (w * 16 + (lane >> 2)) * 4 + ((lane & 3) ^ (lane >> 3)); }
__device__ __forceinline__ uint32_t img_line(uint32_t w, uint32_t lane) { return (lane >> 3) * 256 + w * 64 + (lane & 7) * 8; }

template <int MULTICAST>
__device__ __forceinline__ void tiles(uint32_t bars, const uint2* tab, uint2& nx, int n0, int n1, uint32_t dst, const char* src, uint32_t bytes,
                                      const uint32_t* cnt, uint32_t target, int pace, int head) {
  int due = 0;
#pragma unroll 1
  for (int n = n0; n < n1; n++) {
    const uint2 e = nx;
    nx = tab[n + 1];
    const uint32_t fb = bars + (e.y & 0x3ff);
    mbar_expect_tx(fb, (e.y >> 29) << 13);
    if (e.x & 0x1000000) {
      while ((int32_t)(ld_relaxed_line(cnt + ((e.x >> 25) & 31)) - target) < 0) {}
      asm volatile("fence.acquire.gpu;" ::: "memory"); fence_async_glob();
      if (!MULTICAST) due = since(head);
    }
    mbar_wait(bars + (e.x & 0x7ff), e.x >> 31);
    if (MULTICAST) bulk_g2s_mc(dst + (e.y & 0x3c000), src + (e.x & 0x3fc000), bytes, fb);
    else {
      until(due, (n - n0) * pace);
      bulk_g2s(dst + (e.y & 0x3c000), src + (e.x & 0x3fc000), bytes, fb);
    }
  }
}

template <int BOXES>
__device__ __forceinline__ void weights(uint32_t sb, uint2& nx, int& n, const CUtensorMap* m0, const CUtensorMap* m1, const CUtensorMap* m2, int c0, int c1, int c2, int dk) {
  const uint32_t bars = sb + BAR_OFF;
#pragma unroll 1
  for (bool more = true; more; n++) {
    const uint2 e = nx;
    nx = c_w[0][n + 1];
    more = !(e.y & 0x20000);
    const uint32_t fb = bars + (e.y & 0x3ff), dst = sb + W_OFF + (e.y & 0x1e000);
    const int k0 = (e.y >> 24) + dk;
    if (e.x & 0x7ff) mbar_wait(bars + (e.x & 0x7ff), (e.x >> 15) & 1);
    mbar_wait(bars + ((e.x >> 16) & 0x7ff), e.x >> 31);
    if (BOXES == 2) { tma5d_once(dst, m0, fb, c0, k0); tma5d_once(dst + 8192, m1, fb, c1, k0); }
    else { tma5d(dst, m0, fb, c0, k0); tma5d(dst + 8192, m1, fb, c1, k0); tma5d(dst + 16384, m2, fb, c2, k0); }
  }
}

__device__ __forceinline__ void mod_slice(uint32_t sb, uint32_t* dst, uint32_t tag, uint32_t w, uint32_t lane) {
  float e[4];
#pragma unroll 1
  for (int kb = 0; kb < 4; kb++) {
    mbar_wait(sb + BAR_OFF + B_SL + 8 * kb, 0);
    wg_fence();
#pragma unroll
    for (int q = 0; q < 4; q++) wgmma_n8(e, make_desc(SMEM_BASE + SL_OFF + kb * 8192, 8192) + q * 128, make_desc(SMEM_BASE + TAB_OFF + 4096 + kb * 256, 16) + q * 2, kb | q);
    wg_commit();
  }
  wg_wait<0>();
  fence_regs(e);
  if ((lane & 3) == 0) { st_relaxed(dst + w * 16 + (lane >> 2), tagf(e[0], tag)); st_relaxed(dst + w * 16 + 8 + (lane >> 2), tagf(e[2], tag)); }
  if (w == 0 && lane == 0) mbar_arrive(sb + BAR_OFF + B_SLE);
  __syncwarp();
}

__device__ __forceinline__ int mod_group(int job, int hc) { return (job >> 1) * 16 + hc * 4 + (job & 1) * 2; }

template <bool BY_SM>
__global__ void __cluster_dims__(2, 1, 1) __launch_bounds__(NTHREADS, 1) fused_kernel(const Ptrs Q, const __grid_constant__ Params P) {
  extern __shared__ __align__(1024) uint8_t smem_raw[];
  const int t0 = (int)clock();
  int cta = blockIdx.x;
  {
    uint32_t smid;
    asm volatile("mov.u32 %0, %%smid;" : "=r"(smid));
    const int tp = smid >> 1;
    const int cl = tp < 32 ? tp : (tp < 60 ? tp + 1 + (tp - 32) / 7 : (tp < 62 ? tp + 4 : (tp - 58) * 8));
    if (BY_SM) cta = cl * 2 + (cta & 1);
    cta = __shfl_sync(~0u, cta, 0);
  }
  const int grp = cta >> 4, j = cta & 15, rank = cta & 1, typ = j >> 3;
  const int wg = __shfl_sync(~0u, (int)threadIdx.x >> 7, 0);
  const int warp = __shfl_sync(~0u, (int)threadIdx.x >> 5, 0);
  const uint32_t sb = mapa(SMEM_BASE, rank), bars = sb + BAR_OFF;
  if (warp == 10 && cta < NCTA && elect_one()) {
    prefetch_tmap(&P.mWm2);
#pragma unroll
    for (int i = 0; i < 4; i++) mbar_init(bars + B_SL + 8 * i, 1);
    fence_async_smem();
    if (cta < 64) {
#pragma unroll
      for (int i = 0; i < 4; i++) {
        mbar_expect_tx(bars + B_SL + 8 * i, 8192);
        tma2d_once(sb + SL_OFF + i * 8192, &P.mWm2, bars + B_SL + 8 * i, ((cta >> 4) & 1) * D_ + (cta >> 5) * 256 + ((cta >> 2) & 3) * 64, (cta & 3) * 256 + i * 64);
      }
    }
  }
  __syncwarp();

  if (cta >= NCTA) {
    const uint32_t lane = tid_now() & 31, cf = sb + 196608, hb = cf + 16384;
    const int hc = cta - NCTA;
    if (threadIdx.x == 0) {
#pragma unroll 1
      for (int i = 0; i < 48; i++) mbar_init(hb + 8 * i, 1);
#pragma unroll 1
      for (int i = 0; i < 24; i++) mbar_init(bars + 8 * i, (i >> 1) == 6 ? 4 : 1);
    }
    const uint32_t ep = ld_relaxed(&Q.s->ep[cta * 32 + lane]) + 1;
#pragma unroll 1
    for (int kb = warp; kb < 16; kb += 12) {
      const uint32_t cv = ((const uint32_t*)Q.c)[kb * 32 + lane];
      sts32(cf + kb * 256 + (lane & 3) * 4 + (((lane >> 2) ^ ((2 * kb) & 7)) << 4), pack_bf16(silu_f(bf_lo(cv)), silu_f(bf_hi(cv))));
    }
    fence_async_smem();
    __syncthreads();
    if (wg == 2) {
      if (elect_one()) {
        spin(DELAY_HELP);
        uint32_t s = warp & 3, ph = 1;
#pragma unroll 1
        for (int n = (warp >> 1) & 1; n < 8 * 16; n += 2) {
          mbar_wait(hb + 8 * (24 + s), ph);
          mbar_expect_tx(hb + 8 * s, 8192);
          tma2d_once(sb + s * 8192, &P.mWm2, hb + 8 * s, (32 + mod_group(n >> 4, hc) + (warp & 1)) * 64, (n & 15) * 64);
          s += 4; if (s >= 24) { s -= 24; ph ^= 1; }
        }
      }
      __syncwarp();
      if (warp == 8) Q.s->ep[cta * 32 + lane] = ep;
    } else {
      uint32_t s = wg, ph = 0;
#pragma unroll 1
      for (int job = 0; job < 8; job++) {
        float e[4];
#pragma unroll 1
        for (int kb = 0; kb < 16; kb += 4) {
#pragma unroll 1
          for (int i = 0; i < 4; i++) {
            mbar_wait(hb + 8 * (s + 2 * i), ph);
            wg_fence();
#pragma unroll
            for (int q = 0; q < 4; q++)
              wgmma_n8(e, make_desc(SMEM_BASE, 8192) + (s + 2 * i) * 512 + q * 128, make_desc(SMEM_BASE + 196608, 16) + (kb + i) * 16 + q * 2, kb | i | q);
            wg_commit();
          }
          wg_wait<0>();
          if ((warp & 3) == 0 && elect_one()) {
#pragma unroll
            for (int i = 0; i < 4; i++) mbar_arrive(hb + 8 * (24 + s + 2 * i));
          }
          s += 8; if (s >= 24) { s -= 24; ph ^= 1; }
        }
        fence_regs(e);
        if ((lane & 3) == 0) {
          uint32_t* dst = Q.s->modp + (mod_group(job, hc) + wg) * 64 + (warp & 3) * 16 + (lane >> 2);
          st_relaxed(dst, tagf(e[0], tag_of(ep))); st_relaxed(dst + 8, tagf(e[2], tag_of(ep)));
          const uint32_t g = pack_bf16(2.f * __uint_as_float(tagf(e[0], tag_of(ep))), 2.f * __uint_as_float(tagf(e[2], tag_of(ep))));
          const uint32_t a = sb + PAR_OFF + ((job & 1) * 4 + wg * 2 + ((warp >> 1) & 1)) * 64 + (lane >> 3) * 16 + (warp & 1) * 8 + ((lane >> 2) & 1) * 2;
          asm volatile("st.shared.u16 [%0], %1;\nst.shared.u16 [%0 + 4], %2;" ::"r"(a), "h"((uint16_t)g), "h"((uint16_t)(g >> 16)) : "memory");
        }
        __syncwarp();
      }
    }
    __syncthreads();
    if (warp == 8) {
      if (only_one()) {
        mbar_expect_tx(bars + 64, N_HK * 32768);
#pragma unroll 1
        for (int i = 0; i < 4 * N_HK; i++) tma5d(sb + i * 8192, &P.mWd, bars + 64, hc * 256 + (i & 3) * 64, (i >> 2) * 2);
        uint32_t n = 0;
#pragma unroll 1
        for (int rb = 0; rb < 16; rb++) {
          while ((int32_t)(ld_relaxed(Q.s->cnt + (rb & 7) * 32 + (rb < 8 ? G_HK : 8 + G_ACT)) - (rb < 8 ? 4 * N_HK : 64) * ep) < 0) __nanosleep(50);
          asm volatile("fence.acquire.gpu;" ::: "memory"); fence_async_glob();
#pragma unroll 1
          for (int i = 0; i < 2 * N_HK; i++, n++) {
            mbar_wait(bars + 128 + 8 * (n & 7), ((n >> 3) & 1) ^ 1);
            mbar_expect_tx(bars + 8 * (n & 7), 8192);
            bulk_g2s(sb + 98304 + (n & 7) * 8192, Q.s->img + (size_t)((rb & 7) * N_TILES + T_ACT + (rb >> 3) * 56 + i % N_HK) * 1024 + i / N_HK * 512, 8192, bars + 8 * (n & 7));
          }
        }
      }
    } else if (warp >= 10) {
      if (only_one()) {
        const int q = warp & 1;
#pragma unroll 1
        for (int rb = 0; rb < 16; rb++) {
          mbar_wait(bars + 96 + 8 * q, rb & 1);
#pragma unroll 1
          for (int i = 0; i < 8; i++)
            asm volatile("cp.reduce.async.bulk.global.shared::cta.bulk_group.add.noftz.bf16 [%0], [%1], 4096;"
                         ::"l"(Q.s->img + (size_t)((rb & 7) * N_TILES + T_X1 + (rb >> 3) * 16 + hc * 4 + (i >> 1)) * 1024 + q * 512 + (i & 1) * 256), "r"(sb + 163840 + q * 32768 + i * 4096) : "memory");
          bulk_commit();
          bulk_wait_read();
          mbar_arrive(bars + 80 + 8 * q);
        }
        asm volatile("cp.async.bulk.wait_group 0;" ::: "memory");
        fence_async_glob(); asm volatile("fence.acq_rel.gpu;" ::: "memory");
#pragma unroll 1
        for (int i = 0; i < 8; i++) red_relaxed(Q.s->cnt + i * 32 + G_X1, 8);
      }
    } else if (wg < 2) {
      const uint32_t w = warp & 3;
      uint32_t n = wg * N_HK;
      mbar_wait(bars + 64, 0);
#pragma unroll 1
      for (int rb = 0; rb < 16; rb++) {
        float acc[128];
        mbar_wait(bars + 112 + 8 * wg, (rb & 1) ^ wg ^ 1);
#pragma unroll 1
        for (int kb = 0; kb < N_HK; kb++, n++) {
          mbar_wait(bars + 8 * (n & 7), (n >> 3) & 1);
          const uint32_t da = make_desc(SMEM_BASE + 98304, 16) + (n & 7) * 512, db = make_desc(SMEM_BASE, 8192) + kb * 2048;
          wg_fence();
#pragma unroll
          for (int q = 0; q < 4; q++) wg_n256<H64, H128>(acc, da + qa(q), db + 128 * q, q ? 1 : kb);
          wg_commit();
          wg_wait<1>();
          if (kb && w == 0 && elect_one()) mbar_arrive(bars + 128 + 8 * ((n - 1) & 7));
        }
        if (w == 0 && elect_one()) mbar_arrive(bars + 120 - 8 * wg);
        wg_wait<0>();
        if (w == 0 && elect_one()) mbar_arrive(bars + 128 + 8 * ((n - 1) & 7));
        mbar_wait(bars + 80 + 8 * wg, (rb & 1) ^ 1);
        fence_regs(acc);
        const uint32_t ln = tid_now() & 31, st = sb + 163840 + wg * 32768 + img_pos(w, ln) * 16;
        uint4 gn = lds128(sb + PAR_OFF + (ln & 3) * 16);
#pragma unroll
        for (int c = 0; c < 8; c++) {
          const uint4 g = gn;
          if (c < 7) gn = lds128(sb + PAR_OFF + (c + 1) * 64 + (ln & 3) * 16);
#pragma unroll
          for (int f = 0; f < 2; f++) {
            const float* a = &acc[16 * c + 2 * f];
            sts128(st + c * 4096 + f * 512, hmul2_bf16(g.x, pack_bf16(a[0], a[1])), hmul2_bf16(g.y, pack_bf16(a[4], a[5])),
                   hmul2_bf16(g.z, pack_bf16(a[8], a[9])), hmul2_bf16(g.w, pack_bf16(a[12], a[13])));
          }
        }
        n += N_HK;
        fence_async_smem(); __syncwarp();
        if (elect_one()) mbar_arrive(bars + 96 + 8 * wg);
      }
    }
  } else if (wg < 2) {
    asm volatile("setmaxnreg.inc.sync.aligned.u32 232;");
    const int w = warp & 3, rb = wg * 8 + grp;
    uint4* const img = Q.s->img + (size_t)grp * (N_TILES * 1024);
    uint32_t* const cnt = Q.s->cnt + grp * 32 + wg * 8;
    {
      const uint32_t tid = tid_now() & 127, lane = tid & 31;
      const uint32_t row = 8 * j + 2 * w + (lane >> 4);
      if (tid < 64) st_relaxed_b64(Q.s->stat + ((rb * 2 + rank) * 8 + (j >> 1)) * 64 + tid, 0, 0);
      uint4* dst = img + (T_H + wg * 16 + ((lane >> 3) & 1)) * 1024 + row * 8 + ((lane ^ row) & 7);
      const uint4* back = img + (T_H + wg * 16 + (lane >> 1)) * 1024 + (8 * j + 2 * w + (lane & 1)) * 8;
      const uint32_t tab = sb + TAB_OFF + (lane & 15) * 16;
      if (wg) {
        const uint32_t ep0 = ld_relaxed(&Q.s->ep[cta * 32 + lane]);
        uint32_t* mdst = Q.s->mod0 + ((cta >> 5) * 4 + (cta & 3)) * 512 + ((cta >> 2) & 7) * 64;
        const uint32_t cv = ldg32(Q.c + (cta & 3) * 256 + tid * 2);
        if (tid < 64) st_relaxed(mdst + tid, 0);
        uint4* mbox = Q.s->halo + (size_t)(grp * 16 + j) * 128 + tid;
        st_relaxed_v4(mbox, ~0u, ~0u, ~0u, ~0u); st_relaxed_v4(mbox + 128 * 128, ~0u, ~0u, ~0u, ~0u);
        const uint32_t s0 = ld_relaxed(mbox), s1 = ld_relaxed(mbox + 128 * 128);
        named_sync(0, NTHREADS);
        asm volatile("barrier.cluster.arrive.relaxed.aligned;" ::: "memory");
        in_order();
        sts32(sb + TAB_OFF + 4096 + w * 256 + (lane & 3) * 4 + (((lane >> 2) ^ (2 * w)) << 4), pack_bf16(silu_f(bf_lo(opaque(cv))), silu_f(bf_hi(cv))));
        fence_async_smem();
        if (__any_sync(~0u, (opaque(s0) & opaque(s1)) == 0)) __nanosleep(1);
        named_sync(2, 128);
        asm volatile("barrier.cluster.wait.aligned;" ::: "memory");
        const uint32_t ep = tag_of(opaque(ep0) + 1);
        uint4 xa[4];
#pragma unroll
        for (int i = 0; i < 4; i++) xa[i] = make_uint4(0, 0, 0, 0);
#pragma unroll 1
        for (int s = 0; s < 2; s++) {
          if ((cta >> 6) == s) mod_slice(sb, mdst, ep, w, lane);
          until(t0, s ? T_G1 : T_G0);
          const uint4* ms = (const uint4*)Q.s->mod0 + (2 * s + rank) * 512 + tid;
          uint4 p[4];
#pragma unroll
          for (int i = 0; i < 4; i++) p[i] = make_uint4(0, 0, 0, 0);
          uint32_t it = 0;
          do {
#pragma unroll
            for (int i = 0; i < 4; i++) if (tag_bad(p[i], ep)) p[i] = ld_relaxed_v4(ms + i * 128);
          } while (__any_sync(~0u, tag_bad(p[0], ep) | tag_bad(p[1], ep) | tag_bad(p[2], ep) | tag_bad(p[3], ep)) && ++it < POLL_MAX);
#define F4(f) ((__uint_as_float(p[0].f) + __uint_as_float(p[1].f)) + (__uint_as_float(p[2].f) + __uint_as_float(p[3].f)))
          uint32_t c0 = pack_bf16(F4(x), F4(y)), c1 = pack_bf16(F4(z), F4(w));
#undef F4
          if (w >= 2) { c0 = hadd2_bf16(c0, 0x3f803f80u); c1 = hadd2_bf16(c1, 0x3f803f80u); }
          const uint32_t ta = TAB_OFF + (tid >> 6) * 2048 + (2 * s + rank) * 512 + (tid & 63) * 8, peer = mapa(SMEM_BASE, rank ^ 1);
          asm volatile("st.async.weak.shared::cluster.mbarrier::complete_tx::bytes.v2.b32 [%0], {%2,%3}, [%1];" ::"r"(peer + ta), "r"(peer + BAR_OFF + B_ST + 8 * s), "r"(c0), "r"(c1) : "memory");
          sts64(sb + ta, c0, c1);
          if (s == 0) {
            mbar_wait(bars + B_XB, 0);
#pragma unroll
            for (int i = 0; i < 4; i++) xa[i] = lds128(sb + 4 * 16384 + (row & 7) * 2048 + 1024 + i * 256 + (lane & 15) * 16);
            landed(xa[0].x & xa[1].x & xa[2].x & xa[3].x);
          }
          __syncwarp();
          if (elect_one()) mbar_expect_tx(bars + B_ST + 8 * s, 256);
        }
        mbar_wait(bars + B_ST + 8, 0);
        const float m = __uint_as_float(lds32(sb + TAB_OFF + 6144 + tid * 8)), v = __uint_as_float(lds32(sb + TAB_OFF + 6148 + tid * 8));
#pragma unroll
        for (int i = 4; i < 8; i++) {
          const uint4 a = lds128(tab + i * 256), c = lds128(tab + 2048 + i * 256);
#define NRM(x) pack_bf16(fmaf(bf_lo(x), v, m), fmaf(bf_hi(x), v, m))
          stg128(dst - 16384 + i * 2048, hfma2_bf16(NRM(xa[i & 3].x), c.x, a.x), hfma2_bf16(NRM(xa[i & 3].y), c.y, a.y),
                 hfma2_bf16(NRM(xa[i & 3].z), c.z, a.z), hfma2_bf16(NRM(xa[i & 3].w), c.w, a.w));
#undef NRM
        }
        publish(lane >= 16 ? ld_relaxed(back - 16384) : 0, cnt - 8 + G_H1, 1);
      } else {
        named_sync(0, NTHREADS);
        asm volatile("barrier.cluster.arrive.relaxed.aligned;\nbarrier.cluster.wait.aligned;" ::: "memory");
      }
      mbar_wait(bars + B_XB + 8 * wg, 0);
      float d[64], m = 0.f, v = 0.f, m2 = 0.f, v2 = 0.f;
#pragma unroll
      for (int i = 0; i < 8; i++) {
        const uint4 t = lds128(sb + (4 + wg) * 16384 + (row & 7) * 2048 + i * 256 + (lane & 15) * 16);
        const uint32_t x[4] = {t.x, t.y, t.z, t.w};
#pragma unroll
        for (int e = 0; e < 4; e++) {
          const float d0 = bf_lo(x[e]), d1 = bf_hi(x[e]);
          d[8 * i + 2 * e] = d0; d[8 * i + 2 * e + 1] = d1;
          m += d0; m2 += d1; v = fmaf(d0, d0, v); v2 = fmaf(d1, d1, v2);
        }
      }
      m += m2; v += v2;
#pragma unroll
      for (int i = 1; i < 16; i *= 2) { m += __shfl_xor_sync(~0u, m, i); v += __shfl_xor_sync(~0u, v, i); }
      m *= 1.f / D_;
      v = rsqrtf(fmaxf(fmaf(-m, m, v * (1.f / D_)), 0.f) + 1e-5f);
      m = -m * v;
      if (!wg) {
        sts64(sb + TAB_OFF + 6144 + tid * 8, __float_as_uint(m), __float_as_uint(v));
        __syncwarp();
        if (elect_one()) mbar_arrive(bars + B_ST + 8);
      }
      mbar_wait(bars + B_ST, 0);
#pragma unroll
      for (int s = 0; s < 2; s++) {
        if (s > wg) break;
#pragma unroll
        for (int i = 4 * s; i < 4 * s + 4; i++) {
          const uint4 a = lds128(tab + i * 256), c = lds128(tab + 2048 + i * 256);
#define NRM(e) pack_bf16(fmaf(d[8 * i + 2 * e], v, m), fmaf(d[8 * i + 2 * e + 1], v, m))
          stg128(dst + i * 2048, hfma2_bf16(NRM(0), c.x, a.x), hfma2_bf16(NRM(1), c.y, a.y), hfma2_bf16(NRM(2), c.z, a.z), hfma2_bf16(NRM(3), c.w, a.w));
#undef NRM
        }
      }
      publish(wg || lane < 16 ? ld_relaxed(back) : 0, cnt + G_H0, 1);
    }

    Pipe pp;
    pp.tab = c_cons[wg];
    pp.bars = bars; pp.peer_bars = mapa(bars, rank ^ 1); pp.lead = w == 0; pp.prev = 0; pp.ready = false;
    pp.nx = pp.tab[0];
    const uint32_t dA0 = make_desc(SMEM_BASE, 16), dB0 = make_desc(SMEM_BASE + W_OFF, 8192);
    const uint32_t dAo = dA0 + rank * 512, dAp = dA0 + 512 - rank * 512;

    {
      float acc[2][96];
#pragma unroll 1
      for (int n = 0; n < 14; n++) {
        const uint2 e = pp.begin(n);
        const uint32_t da = dA0 + (e.x & 0xffff), db = dB0 + (e.x >> 16);
        wg_fence();
#pragma unroll
        for (int q = 0; q < 4; q++) {
          wg_n192<H128, H128>(acc[0], da + 2 * q, db + 128 * q, q ? 1 : n);
          wg_n192<H128, H128>(acc[1], da + 2 * q + 512, db + 128 * q, q ? 1 : n);
        }
        wg_commit();
        pp.template end<true>(e.y);
      }
      const uint2 e0 = pp.begin(14), e1 = pp.begin(15);
#pragma unroll
      for (int h = 1; h >= 0; h--) {
        wg_fence();
#pragma unroll
        for (int q = 0; q < 4; q++) wg_n192<H128, H128>(acc[h], dA0 + (e0.x & 0xffff) + 2 * q + 512 * h, dB0 + (e0.x >> 16) + 128 * q, 1);
#pragma unroll
        for (int q = 0; q < 4; q++) wg_n192<H128, H128>(acc[h], dA0 + (e1.x & 0xffff) + 2 * q + 512 * h, dB0 + (e1.x >> 16) + 128 * q, 1);
        wg_commit();
        if (h) { wg_wait<1>(); pp.release(pp.prev); }
      }
      if (pp.lead && elect_one()) mbar_arrive(bars + B_Q + 8 * wg);
      const uint2 ea = pp.begin(16);
      const uint32_t lane = tid_now() & 31, g = lane >> 2, t = lane & 3;
      const uint32_t hal = sb + (ea.x & 0xffff) * 16 + w * 2048 + lane * 16;
      uint4* mbox = Q.s->halo + (size_t)(rb * 16 + j) * 128 + lane;
      const bool first = w == 0 && grp == 0;
      uint32_t qp[2][8][2], kp[2][8][2], vp[2][8][2];
      uint4 hk[2][2], hw[2][2];
#pragma unroll
      for (int h = 1; h >= 0; h--) {
        if (h) wg_wait<1>(); else { in_order(); wg_wait<0>(); pp.release(e0.y); pp.release_now(e1.y); }
        fence_regs(acc[h]);
#pragma unroll
        for (int i = 0; i < 8; i++) {
          kp[h][i][1] = pack_bf16(acc[h][32 + 4 * i + 2], acc[h][32 + 4 * i + 3]);
          vp[h][i][1] = pack_bf16(acc[h][64 + 4 * i + 2], acc[h][64 + 4 * i + 3]);
        }
        if (h == 1 && w == 3 && grp < 7) {
#pragma unroll
          for (int d = 0; d < 2; d++) {
            st_relaxed_v4(mbox + 16 * 128 + d * 32, kp[h][4 * d][1], kp[h][4 * d + 1][1], kp[h][4 * d + 2][1], kp[h][4 * d + 3][1]);
            st_relaxed_v4(mbox + 16 * 128 + d * 32 + 64, vp[h][4 * d][1], vp[h][4 * d + 1][1], vp[h][4 * d + 2][1], vp[h][4 * d + 3][1]);
          }
        }
        if (h == 0) {
#pragma unroll
          for (int d = 0; d < 2; d++) {
            hk[0][d] = hw[0][d] = make_uint4(0, 0, 0, 0);
            if (w == 0) { hk[0][d] = ld_relaxed_v4(mbox + d * 32); hw[0][d] = ld_relaxed_v4(mbox + d * 32 + 64); }
          }
        }
#pragma unroll
        for (int i = 0; i < 8; i++) vp[h][i][1] = movm(vp[h][i][1]);
        if (h == 0 || w < 3) {
#pragma unroll
          for (int d = 0; d < 2; d++) {
            sts128(hal + 2048 + h * 8192 + d * 1024, kp[h][4 * d][1], kp[h][4 * d + 1][1], kp[h][4 * d + 2][1], kp[h][4 * d + 3][1]);
            sts128(hal + 2048 + h * 8192 + d * 1024 + 512, vp[h][4 * d][1], vp[h][4 * d + 1][1], vp[h][4 * d + 2][1], vp[h][4 * d + 3][1]);
          }
        }
        if (h == 0) {
          named_sync(1 + wg, 128);
#pragma unroll
          for (int d = 0; d < 2; d++) {
            if (w) { hk[0][d] = lds128(hal + d * 1024); hw[0][d] = lds128(hal + d * 1024 + 512); }
            hk[1][d] = lds128(hal + 8192 + d * 1024); hw[1][d] = lds128(hal + 8192 + d * 1024 + 512);
          }
        }
#pragma unroll
        for (int i = 0; i < 8; i++) {
          kp[h][i][0] = opaque(pack_bf16(acc[h][32 + 4 * i], acc[h][32 + 4 * i + 1]));
          vp[h][i][0] = movm(pack_bf16(acc[h][64 + 4 * i], acc[h][64 + 4 * i + 1]));
          qp[h][i][0] = opaque(pack_bf16(acc[h][4 * i], acc[h][4 * i + 1]));
          qp[h][i][1] = opaque(pack_bf16(acc[h][4 * i + 2], acc[h][4 * i + 3]));
        }
      }
      if (w == 0) {
        for (uint32_t it = 0; grp > 0 && it < POLL_MAX && __any_sync(~0u, empty(hk[0][0]) || empty(hk[0][1]) || empty(hw[0][0]) || empty(hw[0][1])); it++) {
#pragma unroll
          for (int d = 0; d < 2; d++) { hk[0][d] = ld_relaxed_v4(mbox + d * 32); hw[0][d] = ld_relaxed_v4(mbox + d * 32 + 64); }
        }
#pragma unroll
        for (int d = 0; d < 2; d++)
          hw[0][d] = first ? make_uint4(0, 0, 0, 0) : make_uint4(movm(hw[0][d].x), movm(hw[0][d].y), movm(hw[0][d].z), movm(hw[0][d].w));
      }
      const uint32_t hv[2][8] = {{hw[0][0].x, hw[0][0].y, hw[0][0].z, hw[0][0].w, hw[0][1].x, hw[0][1].y, hw[0][1].z, hw[0][1].w},
                                 {hw[1][0].x, hw[1][0].y, hw[1][0].z, hw[1][0].w, hw[1][1].x, hw[1][1].y, hw[1][1].z, hw[1][1].w}};
      landed(hw[0][0].x & hw[0][1].x & hw[1][0].x & hw[1][1].x);
      float s0[4][4], s1[4][4], s2[4][4];
#pragma unroll
      for (int c = 3; c >= 0; c--) {
        const int h = c >> 1, b = (c & 1) * 4;
        mma16816z(s1[c], qp[h][b][0], qp[h][b][1], qp[h][b + 1][0], qp[h][b + 1][1], kp[h][b][0], kp[h][b + 1][0]);
        mma16816z(s2[c], qp[h][b][0], qp[h][b][1], qp[h][b + 1][0], qp[h][b + 1][1], kp[h][b][1], kp[h][b + 1][1]);
        mma16816z(s0[c], qp[h][b][0], qp[h][b][1], qp[h][b + 1][0], qp[h][b + 1][1], hk[h][c & 1].x, hk[h][c & 1].y);
      }
#pragma unroll
      for (int c = 3; c >= 0; c--) {
        const int h = c >> 1, b = (c & 1) * 4 + 2;
        mma16816(s1[c], qp[h][b][0], qp[h][b][1], qp[h][b + 1][0], qp[h][b + 1][1], kp[h][b][0], kp[h][b + 1][0]);
        mma16816(s2[c], qp[h][b][0], qp[h][b][1], qp[h][b + 1][0], qp[h][b + 1][1], kp[h][b][1], kp[h][b + 1][1]);
        mma16816(s0[c], qp[h][b][0], qp[h][b][1], qp[h][b + 1][0], qp[h][b + 1][1], hk[h][c & 1].z, hk[h][c & 1].w);
      }
      arrive_after(bars + B_R + 16 * wg, s0[0][0]);
      const bool c0 = 2 * t <= g, c1 = 2 * t + 1 <= g;
      const uint32_t mcur = (c0 ? 0x0000ffffu : 0u) | (c1 ? 0xffff0000u : 0u);
      uint32_t pa[4], pb[4];
#pragma unroll
      for (int c = 3; c >= 0; c--) {
        if (c < 2 && first) { s0[c][0] = -INFINITY; s0[c][1] = -INFINITY; }
        float a0 = c0 ? s1[c][0] : s0[c][0], a1 = c1 ? s1[c][1] : s0[c][1];
        float b0 = c0 ? s2[c][2] : s1[c][2], b1 = c1 ? s2[c][3] : s1[c][3];
        const float ma = quad_max(fmaxf(a0, a1)), mb = quad_max(fmaxf(b0, b1));
        a0 = ex2((a0 - ma) * ATT_SCALE_LOG2E); a1 = ex2((a1 - ma) * ATT_SCALE_LOG2E);
        b0 = ex2((b0 - mb) * ATT_SCALE_LOG2E); b1 = ex2((b1 - mb) * ATT_SCALE_LOG2E);
        const float ia = rcp(quad_sum(a0 + a1)), ib = rcp(quad_sum(b0 + b1));
        pa[c] = opaque(pack_bf16(a0 * ia, a1 * ia)); pb[c] = opaque(pack_bf16(b0 * ib, b1 * ib));
      }
      if (pp.lead) { mbar_wait(bars + B_R + 16 * wg, 0); pp.release(ea.y); }
      float o[16][4];
#pragma unroll
      for (int i = 0; i < 16; i++) mma16816z(o[i], pa[i >> 2] & mcur, pb[i >> 2] & ~mcur, 0u, pb[i >> 2] & mcur, vp[i >> 3][i & 7][0], vp[i >> 3][i & 7][1]);
#pragma unroll
      for (int i = 0; i < 16; i++) mma1688(o[i], pa[i >> 2] & ~mcur, 0u, hv[i >> 3][i & 7]);
      arrive_after(bars + B_R + 16 * wg + 8, o[15][0]);
      uint4* tile = img + (T_O + wg * 16 + j) * 1024;
      uint4* dst = tile + img_pos(w, lane);
#pragma unroll
      for (int c = 0; c < 4; c++)
#pragma unroll
        for (int f = 0; f < 2; f++) {
          stg128(dst + c * 256 + f * 32, pack_bf16(o[4 * c][2 * f], o[4 * c][2 * f + 1]), pack_bf16(o[4 * c + 1][2 * f], o[4 * c + 1][2 * f + 1]),
                 pack_bf16(o[4 * c + 2][2 * f], o[4 * c + 2][2 * f + 1]), pack_bf16(o[4 * c + 3][2 * f], o[4 * c + 3][2 * f + 1]));
        }
      publish(ld_relaxed(tile + img_line(w, lane)), cnt + G_O, 1);
    }

    {
      float acc[2][64];
      uint32_t xr[32];
      {
        const uint32_t lane = tid_now() & 31;
        const uint2 e = pp.begin(17);
        const uint32_t a0 = sb + (e.x & 0xffff) * 16 + (w * 16 + (lane & 15)) * 128 + (((lane >> 4) ^ (lane & 7)) << 4);
#pragma unroll
        for (int i = 0; i < 8; i++) ldsm4((a0 ^ ((i & 3) << 5)) + (i >> 2) * 8192, xr[4 * i], xr[4 * i + 1], xr[4 * i + 2], xr[4 * i + 3]);
        landed(xr[0] & xr[4] & xr[8] & xr[12] & xr[16] & xr[20] & xr[24] & xr[28]);
        named_sync(1 + wg, 128);
        pp.release(e.y);
      }
      pp.prev = 0;
#pragma unroll 1
      for (int n = 18; n < 24; n++) {
        const uint2 e = pp.begin(n);
        const uint32_t da = e.x & 0xffff, db = dB0 + (e.x >> 16);
        wg_fence();
#pragma unroll
        for (int q = 0; q < 4; q++) {
          wg_n128<H64, H128>(acc[0], dAo + da + qa(q), db + 128 * q, q ? 1 : n - 18);
          wg_n128<H64, H128>(acc[1], dAp + da + qa(q), db + 128 * q, q ? 1 : n - 18);
        }
        wg_commit();
        pp.template end<true>(e.y);
      }
      const uint2 e0 = pp.begin(24);
      const uint2 e1 = pp.begin(25);
#pragma unroll
      for (int h = 1; h >= 0; h--) {
        wg_fence();
#pragma unroll
        for (int q = 0; q < 4; q++) wg_n128<H64, H128>(acc[h], (h ? dAp : dAo) + (e0.x & 0xffff) + qa(q), dB0 + (e0.x >> 16) + 128 * q, 1);
#pragma unroll
        for (int q = 0; q < 4; q++) wg_n128<H64, H128>(acc[h], (h ? dAp : dAo) + (e1.x & 0xffff) + qa(q), dB0 + (e1.x >> 16) + 128 * q, 1);
        wg_commit();
      }
      const uint32_t tid = tid_now() & 127, lane = tid & 31;
      const uint2 ea = pp.begin(26);
      const uint32_t px = (ea.x & 0xffff) * 16 + tid * 16;
      wg_wait<1>();
      pp.release_now(pp.prev);
      fence_regs(acc[1]);
#pragma unroll
      for (int i = 0; i < 8; i++)
        st_async(pp.peer_bars - BAR_OFF + px + i * 2048, pp.peer_bars + (pp.nx.y & 0x3ff), pack_bf16(acc[1][8 * i], acc[1][8 * i + 1]), pack_bf16(acc[1][8 * i + 2], acc[1][8 * i + 3]),
                 pack_bf16(acc[1][8 * i + 4], acc[1][8 * i + 5]), pack_bf16(acc[1][8 * i + 6], acc[1][8 * i + 7]));
      wg_wait<0>();
      pp.release(e0.y); pp.release(e1.y); pp.release_now(ea.y);
      fence_regs(acc[0]);
      const uint32_t ep = tag_of(lds32(bars + ROLE_OFF + 4));
      mbar_wait(bars + B_PAR, 0);
      uint32_t pr[3][16];
#pragma unroll
      for (int i = 0; i < 4; i++) {
        const uint4 x = lds128(sb + PAR_OFF + (i >> 2) * 256 + (lane & 3) * 64 + (i & 3) * 16);
        pr[i >> 2][(i & 3) * 4] = x.x; pr[i >> 2][(i & 3) * 4 + 1] = x.y; pr[i >> 2][(i & 3) * 4 + 2] = x.z; pr[i >> 2][(i & 3) * 4 + 3] = x.w;
      }
      const uint2 eb = pp.begin(27);
      float sm[2] = {0.f, 0.f}, sq[2] = {0.f, 0.f};
#pragma unroll
      for (int c = 0; c < 8; c++) {
        const uint4 z = lds128(sb + px + c * 2048);
        const uint32_t zz[4] = {z.x, z.y, z.z, z.w};
#pragma unroll
        for (int b = 0; b < 4; b++) {
          const int i = 4 * c + b;
          xr[i] = hfma2_bf16(pr[0][i >> 1], hadd2_bf16(pack_bf16(acc[0][2 * i], acc[0][2 * i + 1]), zz[b]), xr[i]);
          const float d0 = bf_lo(xr[i]), d1 = bf_hi(xr[i]);
          acc[0][2 * i] = d0; acc[0][2 * i + 1] = d1;
          sm[i & 1] += d0 + d1;
          sq[i & 1] = fmaf(d0, d0, fmaf(d1, d1, sq[i & 1]));
        }
      }
      {
        const bool b0 = lane & 1;
        sm[0] = (b0 ? sm[1] : sm[0]) + __shfl_xor_sync(~0u, b0 ? sm[0] : sm[1], 1);
        sq[0] = (b0 ? sq[1] : sq[0]) + __shfl_xor_sync(~0u, b0 ? sq[0] : sq[1], 1);
        sm[0] += __shfl_xor_sync(~0u, sm[0], 2);
        sq[0] += __shfl_xor_sync(~0u, sq[0], 2);
      }
      uint2* ss = Q.s->stat + (rb * 2 + rank) * 512 + w * 16 + (lane >> 2) * 2 + (lane & 1);
      if (!(lane & 2)) st_relaxed_b64(ss + (j >> 1) * 64, tagf(sm[0], ep), tagf(sq[0], ep));
      named_sync(1 + wg, 128);
      pp.release(eb.y);
      mbar_wait(bars + B_PAR + 8, 0);
#pragma unroll
      for (int i = 4; i < 12; i++) {
        const uint4 x = lds128(sb + PAR_OFF + (i >> 2) * 256 + (lane & 3) * 64 + (i & 3) * 16);
        pr[i >> 2][(i & 3) * 4] = x.x; pr[i >> 2][(i & 3) * 4 + 1] = x.y; pr[i >> 2][(i & 3) * 4 + 2] = x.z; pr[i >> 2][(i & 3) * 4 + 3] = x.w;
      }
      {
        ss += (lane & 2) * 128;
        uint2 p[4];
#pragma unroll
        for (int i = 0; i < 4; i++) p[i] = make_uint2(0, 0);
        spin(DELAY_ST);
        uint32_t it = 0, bad;
        do {
          bad = 0;
#pragma unroll
          for (int i = 0; i < 4; i++) if (((p[i].x ^ ep) | (p[i].y ^ ep)) & 3u) p[i] = ld_relaxed_b64(ss + i * 64);
#pragma unroll
          for (int i = 0; i < 4; i++) bad |= (p[i].x ^ ep) | (p[i].y ^ ep);
        } while (__any_sync(~0u, bad & 3u) && ++it < POLL_MAX);
        float m = (__uint_as_float(p[0].x) + __uint_as_float(p[1].x)) + (__uint_as_float(p[2].x) + __uint_as_float(p[3].x));
        float v = (__uint_as_float(p[0].y) + __uint_as_float(p[1].y)) + (__uint_as_float(p[2].y) + __uint_as_float(p[3].y));
        m += __shfl_xor_sync(~0u, m, 2); v += __shfl_xor_sync(~0u, v, 2);
        m *= 1.f / D_;
        v = rsqrtf(fmaxf(fmaf(-m, m, v * (1.f / D_)), 0.f) + 1e-5f);
        m = -m * v;
#pragma unroll
        for (int r = 0; r < 2; r++) { sm[r] = __shfl_sync(~0u, m, r, 2); sq[r] = __shfl_sync(~0u, v, r, 2); }
      }
      uint4* tile = img + (T_H + wg * 16 + (j & 14)) * 1024 + rank * 512;
      uint4* dst = tile + img_pos(w, lane);
#pragma unroll
      for (int c = 0; c < 4; c++)
#pragma unroll
        for (int f = 0; f < 2; f++) {
          uint32_t y[4];
#pragma unroll
          for (int b = 0; b < 4; b++) {
            const int i = c * 4 + b;
            y[b] = hfma2_bf16(pack_bf16(fmaf(acc[0][4 * i + 2 * f], sq[f], sm[f]), fmaf(acc[0][4 * i + 2 * f + 1], sq[f], sm[f])), pr[2][i], pr[1][i]);
          }
          stg128(dst + (c >> 1) * 1024 + (c & 1) * 256 + f * 32, y[0], y[1], y[2], y[3]);
        }
      publish(ld_relaxed(tile + img_line(w, lane) + (lane >> 4) * 512), cnt + G_H2, 1);
#pragma unroll
      for (int c = 0; c < 4; c++)
#pragma unroll
        for (int f = 0; f < 2; f++) {
          stg128(dst + (T_X1 - T_H + (c >> 1)) * 1024 + (c & 1) * 256 + f * 32, xr[8 * c + f], xr[8 * c + 2 + f], xr[8 * c + 4 + f], xr[8 * c + 6 + f]);
        }
    }

    float acc[2][64], ax[32];
    uint32_t px_y;
    {
      float a3[2][96];
      pp.prev = 0;
#pragma unroll 1
      for (int n = 28; n < 44; n++) {
        const uint2 e = pp.begin(n);
        const uint32_t da = e.x & 0xffff, db = dB0 + (e.x >> 16);
        wg_fence();
#pragma unroll
        for (int q = 0; q < 4; q++) {
          wg_n192<H64, H128>(a3[0], dAo + da + qa(q), db + 128 * q, q ? 1 : n - 28);
          wg_n192<H64, H128>(a3[1], dAp + da + qa(q), db + 128 * q, q ? 1 : n - 28);
        }
        wg_commit();
        pp.end(e.y);
      }
      px_y = pp.nx.y;
      pp.nx = pp.tab[45]; pp.ready = false;
      mbar_wait(bars + ((px_y >> 16) & 0x7ff), px_y >> 31);
      wg_wait<0>();
      pp.release_now(pp.prev);
      fence_regs(a3[0]); fence_regs(a3[1]);
      pp.prev = 0;
#pragma unroll
      for (int i = 0; i < 4; i++)
        st_async(pp.peer_bars - 8192 + (tid_now() & 127) * 16 + i * 2048, pp.peer_bars + (px_y & 0x3ff), pack_bf16(a3[1][64 + 8 * i], a3[1][65 + 8 * i]),
                 pack_bf16(a3[1][66 + 8 * i], a3[1][67 + 8 * i]), pack_bf16(a3[1][68 + 8 * i], a3[1][69 + 8 * i]), pack_bf16(a3[1][70 + 8 * i], a3[1][71 + 8 * i]));
#pragma unroll
      for (int i = 0; i < 64; i++) { acc[0][i] = a3[0][i]; acc[1][i] = a3[1][i]; }
#pragma unroll
      for (int i = 0; i < 32; i++) ax[i] = a3[0][64 + i];
    }
    uint32_t seen, seen2;
#pragma unroll 1
    for (int T = 0;; T++) {
      wg_wait<0>();
      pp.release_now(pp.prev);
      fence_regs(acc[0]); fence_regs(acc[1]);
      pp.prev = 0;
      {
        const uint32_t lane = tid_now() & 31;
        uint4* tile = img + (T_ACT + wg * 56 + (T ? 8 + 16 * T : 0) + j) * 1024;
        uint4* tx = img + (T_ACT + wg * 56 + 16 + (j >> 1)) * 1024 + rank * 512;
        const int ts = (int)clock();
#pragma unroll
        for (int c = 0; c < 4; c++)
#pragma unroll
          for (int f = 0; f < 2; f++) {
            uint32_t y[4];
#pragma unroll
            for (int b = 0; b < 4; b++) {
              const int i = ((c & 1) * 4 + b) * 4 + 2 * f;
              y[b] = pack_bf16(swiglu(acc[c >> 1][i], acc[c >> 1][i] * acc[c >> 1][32 + i]), swiglu(acc[c >> 1][i + 1], acc[c >> 1][i + 1] * acc[c >> 1][33 + i]));
            }
            stg128(tile + img_pos(w, lane) + ((c >> 1) ^ rank) * 512 + (c & 1) * 256 + f * 32, y[0], y[1], y[2], y[3]);
            if (c + f < 4) until(ts, (2 * c + f + 1) * P_ACT);
            fence_regs(acc[0]); fence_regs(acc[1]);
          }
        if (T == 0) {
          if (wg == 0 && j < N_HK) publish(ld_relaxed(tile + img_line(w, lane)), cnt + G_HK, 1);
          mbar_wait(bars + (px_y & 0x3ff), 1);
          uint32_t z[16];
#pragma unroll
          for (int i = 0; i < 4; i++) { const uint4 x = lds128(bars - 8192 + (tid_now() & 127) * 16 + i * 2048); z[4 * i] = x.x; z[4 * i + 1] = x.y; z[4 * i + 2] = x.z; z[4 * i + 3] = x.w; }
          landed(z[0] & z[4] & z[8] & z[12]);
          named_sync(1 + wg, 128);
          pp.release(px_y);
#pragma unroll
          for (int c = 0; c < 2; c++)
#pragma unroll
            for (int f = 0; f < 2; f++) {
              uint32_t y[4];
#pragma unroll
              for (int b = 0; b < 4; b++) {
                const int i = (c * 4 + b) * 2 + f;
                const float o0 = bf_lo(z[i]), o1 = bf_hi(z[i]);
                y[b] = pack_bf16(swiglu(rank ? o0 : ax[2 * i], o0 * ax[2 * i]), swiglu(rank ? o1 : ax[2 * i + 1], o1 * ax[2 * i + 1]));
              }
              stg128(tx + img_pos(w, lane) + c * 256 + f * 32, y[0], y[1], y[2], y[3]);
            }
        }
        seen = ld_relaxed(tile + img_line(w, lane));
        seen2 = ld_relaxed(tx + img_line(w, lane & 15));
      }
      if (T == 2) break;
      const int n0 = 45 + 16 * T, n1 = n0 + 16;
#pragma unroll 1
      for (int n = n0; n < n1; n++) {
        const uint2 e = pp.begin(n);
        const uint32_t da = e.x & 0xffff, db = dB0 + (e.x >> 16);
        wg_fence();
#pragma unroll
        for (int q = 0; q < 4; q++) {
          wg_n128<H64, H128>(acc[0], dAo + da + qa(q), db + 128 * q, q ? 1 : n - n0);
          wg_n128<H64, H128>(acc[1], dAp + da + qa(q), db + 128 * q, q ? 1 : n - n0);
        }
        wg_commit();
        if (n == n0 + 1) publish(opaque(seen) & opaque(seen2), cnt + G_ACT + T, 1);
        pp.end(e.y);
      }
    }
    {
      uint32_t gp[16];
#pragma unroll
      for (int ph = 0; ph < 2; ph++) {
#pragma unroll 1
        for (int n = ph ? 90 : 77; n < (ph ? N_END - N_PEEL : 90); n++) {
          const uint2 e = pp.begin(n);
          const uint32_t da = dA0 + wg * 512 + (e.x & 0xffff), db = dB0 + (e.x >> 16);
          wg_fence();
#pragma unroll
          for (int q = 0; q < 4; q++) wg_n128<H64, H128>(acc[0], da + qa(q), db + 128 * q, q || ph ? 1 : n - 77);
          wg_commit();
          pp.end(e.y);
        }
        if (ph == 0) {
          publish(opaque(seen) & opaque(seen2), cnt + G_ACT + 2, 1);
          mbar_wait(bars + B_GB, 0);
#pragma unroll
          for (int i = 0; i < 4; i++) {
            const uint4 x = lds128(sb + PAR_OFF + 768 + (tid_now() & 3) * 64 + i * 16);
            gp[4 * i] = x.x; gp[4 * i + 1] = x.y; gp[4 * i + 2] = x.z; gp[4 * i + 3] = x.w;
          }
        }
      }
#pragma unroll
      for (int n = N_END - N_PEEL; n < N_END; n++) {
        const uint2 e = pp.begin(n);
        const uint32_t da = dA0 + wg * 512 + (e.x & 0xffff), db = dB0 + (e.x >> 16);
        wg_fence();
#pragma unroll
        for (int q = 0; q < 4; q++) wg_n128<H64, H128>(acc[0], da + qa(q), db + 128 * q, 1);
        wg_commit();
        if (n == N_END - N_PEEL) { wg_wait<1>(); pp.release(pp.prev); pp.prev = 0; }
      }
      const uint32_t lane = tid_now() & 31;
      uint32_t xp[32];
      {
        const uint2 e0 = pp.begin(N_END), e1 = pp.begin(N_END + 1);
#pragma unroll
        for (int i = 0; i < 8; i++) {
          const uint4 r = lds128(sb + (((i & 4 ? e1.x : e0.x) & 0xffff) + wg * 512 + img_pos(w, lane) + ((i >> 1) & 1) * 256 + (i & 1) * 32) * 16);
          xp[(i >> 1) * 8 + (i & 1)] = r.x; xp[(i >> 1) * 8 + 2 + (i & 1)] = r.y; xp[(i >> 1) * 8 + 4 + (i & 1)] = r.z; xp[(i >> 1) * 8 + 6 + (i & 1)] = r.w;
        }
      }
      const uint32_t st = sb + ((w & 2) ? pp.nx.x >> 16 : pp.nx.x & 0xffff) * 16 + wg * 8192 + (w & 1) * 4096;
      const uint32_t a0 = opaque(st + (lane & 15) * 128 + (((lane >> 4) ^ (lane & 7)) << 4));
      if (pp.lead && elect_one()) mbar_arrive(bars + B_END);
      wg_wait<0>();
      pp.release_now(pp.prev);
      fence_regs(acc[0]);
#pragma unroll
      for (int c = 0; c < 4; c++) {
        uint32_t y[2][4];
#pragma unroll
        for (int f = 0; f < 2; f++)
#pragma unroll
          for (int b = 0; b < 4; b++) {
            const int i = 16 * c + 4 * b + 2 * f;
            y[f][b] = hfma2_bf16(gp[4 * c + b], pack_bf16(acc[0][i], acc[0][i + 1]), xp[8 * c + 2 * b + f]);
          }
        stsm4((a0 ^ ((c & 1) << 6)) + (c >> 1) * 2048, y[0][0], y[1][0], y[0][1], y[1][1]);
        stsm4((a0 ^ ((c & 1) << 6) ^ 32) + (c >> 1) * 2048, y[0][2], y[1][2], y[0][3], y[1][3]);
        if (c == 1) {
          fence_async_smem(); __syncwarp();
          if (elect_one()) {
            tma2d_st(&P.mOut, st, typ * D_ + (j & 7) * 128, grp * 128 + wg * 64 + w * 16);
            bulk_commit();
          }
        }
      }
      {
        __syncwarp();
        const uint32_t ln = tid_now() & 31;
        uint4* op = (uint4*)(Q.out + (size_t)(grp * 256 + 2 * (wg * 64 + w * 16 + (ln >> 3)) + typ) * D_ + (j & 7) * 128 + 64) + (ln & 7);
        uint4 r[4];
#pragma unroll
        for (int k = 0; k < 4; k++) r[k] = lds128(st + 2048 + ((ln >> 3) + 4 * k) * 128 + (((ln & 7) ^ (((ln >> 3) + 4 * k) & 7)) << 4));
#pragma unroll
        for (int k = 0; k < 4; k++) stg128(op + k * D_, r[k].x, r[k].y, r[k].z, r[k].w);
        if (elect_one()) bulk_wait_read();
      }
    }
  } else {
    asm volatile("setmaxnreg.dec.sync.aligned.u32 40;");
    const uint32_t lane = tid_now() & 31;
    if (elect_one()) {
      if (warp == 10) {
        prefetch_tmap(&P.mWqkv);
#pragma unroll
        for (int i = 0; i < 12; i++) mbar_init(bars + 1024 + 8 * i, i < 4 ? 4 : 1);
        mbar_init(bars + B_ST, 4); mbar_init(bars + B_ST + 8, 8); mbar_init(bars + B_XB, 1); mbar_init(bars + B_XB + 8, 1); mbar_init(bars + B_END, 2);
        sts32(bars + ROLE_OFF, cta >> 1);
      } else if (warp == 11) {
#pragma unroll 1
        for (int u = 0; u < 2; u++) {
#pragma unroll
          for (int i = 0; i < 20; i++) mbar_init(bars + u * 512 + 352 + 8 * i, 1 + u);
        }
      } else {
#pragma unroll 22
        for (int i = 0; i < 44; i++) mbar_init(bars + (warp & 1) * 512 + 8 * i, 1 + (warp & 1));
      }
      asm volatile("fence.mbarrier_init.release.cluster;" ::: "memory");
    }
    named_sync(0, NTHREADS);
    asm volatile("barrier.cluster.arrive.relaxed.aligned;" ::: "memory");
    asm volatile("barrier.cluster.wait.aligned;" ::: "memory");
    const uint32_t ep0 = ld_relaxed(&Q.s->ep[cta * 32 + lane]);
    if (!(warp & 1)) {
      if (only_one()) {
        const int q = (warp >> 1) & 1;
        const uint2* tab = c_act[q];
        const char* src = (const char*)(Q.s->img + (size_t)grp * (N_TILES * 1024) + rank * 512);
        const uint32_t sa = sb + rank * 8192;
        if (q) {
          if (cta >= 64) {
#pragma unroll 1
            for (int i = 0; i < 4; i++) {
              until(t0, (cta >= 96 ? T_Q3 : T_Q2) + i * P_Q);
              mbar_expect_tx(bars + B_SL + 8 * i, 8192);
              tma2d_once(sb + SL_OFF + i * 8192, &P.mWm2, bars + B_SL + 8 * i, ((cta >> 4) & 1) * D_ + (cta >> 5) * 256 + ((cta >> 2) & 3) * 64, (cta & 3) * 256 + i * 64);
            }
          }
        }
        mbar_expect_tx(bars + B_XB + 8 * q, 16384);
#pragma unroll 1
        for (int i = 0; i < 8; i++) {
          until(t0, q ? T_XB + i * P_XB : T_XA);
          bulk_g2s(sb + (4 + q) * 16384 + i * 2048, Q.x + (size_t)(cta * 16 + 2 * i + q) * D_, 2048, bars + B_XB + 8 * q);
        }
        const uint32_t target = (opaque(ep0) + 1) * 64;
        const uint32_t* cnt = Q.s->cnt + grp * 32;
        const char* x1 = src + (T_X1 + typ * 16 + (j & 7) * 2) * 16384 + (q - rank) * 8192;
        uint2 nx = tab[0];
#pragma unroll 1
        for (int ph = 0; ph < 4; ph++) {
          const bool half = ph == 3;
          tiles<1>(bars, tab, nx, half ? 77 : (ph ? 11 + 17 * ph : 0), half ? N_END : (ph ? 11 + 33 * ph : 16), half ? sb + q * 8192 + rank * 4096 : sa,
                   half ? src + typ * 56 * 16384 + q * 8192 - rank * 4096 : src, half ? 4096 : 8192, half ? cnt + typ * 8 : cnt, target, 0, 0);
          if (ph == 1) { mbar_expect_tx(bars + (nx.y & 0x3ff), 8192); nx = tab[45]; }
          if (ph) continue;
#pragma unroll 1
          for (int n = 16; n < 28; n++) {
            const uint2 e = nx;
            nx = tab[n + 1];
            const uint32_t fb = bars + (e.y & 0x3ff);
            mbar_wait(bars + (e.x & 0x7ff), e.x >> 31);
            mbar_expect_tx(fb, (e.y >> 29) << 13);
            if (n == 17) {
              tma2d(sb + (e.y & 0x3c000), &P.mX, fb, q * D_ + (j & 14) * 64, grp * 128 + rank * 64);
              tma2d(sb + (e.y & 0x3c000) + 8192, &P.mX, fb, q * D_ + (j | 1) * 64, grp * 128 + rank * 64);
              tiles<0>(bars, tab, nx, 18, 26, sb, src + rank * 8192, 16384, cnt, target, q ? P_G2B : P_G2, q ? F_G2B : F_G2A);
              n = 25;
            }
          }
        }
        while ((int32_t)(ld_relaxed_line(cnt + G_X1) - target) < 0) {}
        asm volatile("fence.acquire.gpu;" ::: "memory"); fence_async_glob();
#pragma unroll 1
        for (int n = 0; n < 2; n++) {
          const uint2 e = tab[N_END + n];
          const uint32_t fb = bars + (e.y & 0x3ff);
          mbar_expect_tx(fb, 8192);
          mbar_wait(bars + (e.x & 0x7ff), e.x >> 31);
          bulk_g2s(sb + q * 8192 + (e.y & 0x3c000), x1 + n * 16384, 8192, fb);
        }
      }
    } else if (warp == 9) {
      if (only_one()) {
        uint2 nx = c_w[0][0];
#pragma unroll 1
        for (int n = 0; n < N_W;) {
          if (n < 5) until(t0, n ? T_W + (n - 1) * P_W : T_W0);
          if (n == 2) mbar_wait(bars + B_SLE, 0);
          if (n == 5) { prefetch_tmap(&P.mWo); prefetch_tmap(&P.mWg); prefetch_tmap(&P.mWu); prefetch_tmap(&P.mWd); prefetch_tmap(&P.mX); }
          const int u = (nx.y >> 10) & 7;
          if (u < 2) {
            weights<3>(sb, nx, n, u ? &P.mWg : &P.mWqkv, u ? &P.mWu : &P.mWqkv, u ? &P.mWg + rank : &P.mWqkv,
                       j * 64, (u ? 0 : D_) + j * 64, u ? 1024 + (j >> 1) * 64 : 2 * D_ + j * 64, 0);
          } else {
            const bool ffn = u == 3 || u == 4;
            const int c0 = ffn ? u * 1024 - 1536 + j * 64 : (u == 2 ? j >> 1 : j & 7) * 128;
            const CUtensorMap* m0 = ffn ? &P.mWg : (u == 2 ? &P.mWo : &P.mWd);
            weights<2>(sb, nx, n, m0, m0 + ffn, nullptr, c0, ffn ? c0 : c0 + 64, 0, u == 2 ? rank * 2 : 0);
          }
        }
        prefetch_tmap(&P.mOut);
      }
    } else {
      {
        const uint32_t i = opaque((grp * 2 + rank) * 8), k = i < N_W - 128 ? i + 128 : 128;
        if ((c_cons[0][i].x & c_cons[1][i].x & c_act[0][i].y & c_act[1][i].y & c_w[0][i].y & c_w[0][k].y) == 0xffffffffu) __trap();
      }
      const uint32_t ep = opaque(ep0) + 1;
      if (lane == 0) {
        sts32(bars + ROLE_OFF + 4, ep);
        uint32_t pr; asm volatile("ld.shared::cluster.u32 %0, [%1];" : "=r"(pr) : "r"(mapa(bars + ROLE_OFF, rank ^ 1)) : "memory");
        if (pr != (uint32_t)(cta >> 1) || sb != smem_u32(smem_raw)) { __trap(); }
      }
      const uint32_t tag = tag_of(ep);
#pragma unroll 1
      for (int i = 0; i < 8; i++) {
        const uint2* src = (const uint2*)(Q.s->modp + (i >> 1) * 1024 + (i < 6 ? j >> 1 : j & 7) * 128 + (i & 1) * 64) + lane;
        uint2 a; uint32_t it = 0;
        do { if (it) __nanosleep(200); a = ld_relaxed_b64(src); guard(++it); } while (__any_sync(~0u, ((a.x ^ tag) | (a.y ^ tag)) & 3u));
        uint32_t p = pack_bf16(__uint_as_float(a.x), __uint_as_float(a.y));
        if ((i >> 1) == 2) p = pack_bf16(1.f + bf_lo(p), 1.f + bf_hi(p));
        const float sc = i < 2 ? 1.f : (i < 6 ? 0.5f : 2.f);
        p = pack_bf16(sc * bf_lo(p), sc * bf_hi(p));
        sts32(sb + PAR_OFF + (i >> 1) * 256 + (lane & 3) * 64 + (i & 1) * 32 + (lane >> 2) * 4, p);
        __syncwarp();
        if ((i == 1 || i == 5 || i == 7) && elect_one()) { mbar_arrive(bars + (i == 7 ? B_GB : B_PAR + (i & 4) * 2)); }
      }
      mbar_wait_bounded(bars + B_R, 0);
      Q.s->ep[cta * 32 + lane] = ep;
      mbar_wait_bounded(bars + B_END, 0);
    }
  }
}

typedef CUresult (*PFN_encodeTiled)(CUtensorMap*, CUtensorMapDataType, cuuint32_t, void*, const cuuint64_t*, const cuuint64_t*,
                                    const cuuint32_t*, const cuuint32_t*, CUtensorMapInterleave, CUtensorMapSwizzle,
                                    CUtensorMapL2promotion, CUtensorMapFloatOOBfill);

void make_map(PFN_encodeTiled enc, CUtensorMap* m, const void* ptr, uint64_t inner, uint64_t outer, uint32_t box_outer, int promo = CU_TENSOR_MAP_L2_PROMOTION_L2_256B) {
  cuuint64_t dims[2] = {inner, outer};
  cuuint64_t strides[1] = {inner * 2};
  cuuint32_t box[2] = {64, box_outer};
  cuuint32_t es[2] = {1, 1};
  enc(m, CU_TENSOR_MAP_DATA_TYPE_BFLOAT16, 2, const_cast<void*>(ptr), dims, strides, box, es, CU_TENSOR_MAP_INTERLEAVE_NONE,
      CU_TENSOR_MAP_SWIZZLE_128B, (CUtensorMapL2promotion)promo, CU_TENSOR_MAP_FLOAT_OOB_FILL_NONE);
}
void make_wmap(PFN_encodeTiled enc, CUtensorMap* m, const void* ptr, uint64_t cols, uint64_t rows, bool permuted) {
  cuuint64_t dims[5] = {cols, 2, 4, 4, rows / 32};
  cuuint64_t strides[4] = {cols * 2, cols * 2 * (permuted ? 8 : 2), cols * 2 * (permuted ? 2 : 8), cols * 2 * 32};
  cuuint32_t box[5] = {64, 2, 4, 4, 2};
  cuuint32_t es[5] = {1, 1, 1, 1, 1};
  enc(m, CU_TENSOR_MAP_DATA_TYPE_BFLOAT16, 5, const_cast<void*>(ptr), dims, strides, box, es, CU_TENSOR_MAP_INTERLEAVE_NONE,
      CU_TENSOR_MAP_SWIZZLE_128B, CU_TENSOR_MAP_L2_PROMOTION_L2_128B, CU_TENSOR_MAP_FLOAT_OOB_FILL_NONE);
}

}

extern "C" void kernel_launch(void* const* d_in, const int* in_sizes, int n_in, void* d_out, int out_size) {
  (void)in_sizes; (void)n_in; (void)out_size;
  static PFN_encodeTiled enc = nullptr;
  static void* scratch = nullptr;
  static int sms = 0;
  if (!enc) {
    int dev = 0;
    cudaGetDevice(&dev);
    cudaDeviceGetAttribute(&sms, cudaDevAttrMultiProcessorCount, dev);
    cudaGetSymbolAddress(&scratch, g_s);
    void* fn = nullptr;
    cudaDriverEntryPointQueryResult q;
    cudaGetDriverEntryPoint("cuTensorMapEncodeTiled", &fn, cudaEnableDefault, &q);
    enc = (PFN_encodeTiled)fn;
    cudaFuncSetAttribute(fused_kernel<true>, cudaFuncAttributeMaxDynamicSharedMemorySize, SMEM_BYTES);
    cudaFuncSetAttribute(fused_kernel<false>, cudaFuncAttributeMaxDynamicSharedMemorySize, SMEM_BYTES);
  }
  Params P;
  make_wmap(enc, &P.mWqkv, d_in[1], 3 * D_, D_, false);
  make_wmap(enc, &P.mWo, d_in[2], D_, D_, true);
  make_wmap(enc, &P.mWg, d_in[4], F_, D_, true);
  make_wmap(enc, &P.mWu, d_in[5], F_, D_, true);
  make_wmap(enc, &P.mWd, d_in[6], D_, F_, true);
  make_map(enc, &P.mOut, d_out, 2 * D_, S_ / 2, 16);
  make_map(enc, &P.mX, d_in[0], 2 * D_, S_ / 2, 64, CU_TENSOR_MAP_L2_PROMOTION_L2_128B);
  make_map(enc, &P.mWm2, d_in[8], 6 * D_, D_, 64, CU_TENSOR_MAP_L2_PROMOTION_L2_128B);
  Ptrs Q;
  Q.s = (Scratch*)scratch;
  Q.x = (const __nv_bfloat16*)d_in[0];
  Q.c = (const __nv_bfloat16*)d_in[7];
  Q.out = (__nv_bfloat16*)d_out;
  if (sms == NCTA + 4) fused_kernel<true><<<NCTA + 4, NTHREADS, SMEM_BYTES, cudaStreamPerThread>>>(Q, P);
  else fused_kernel<false><<<NCTA + 4, NTHREADS, SMEM_BYTES, cudaStreamPerThread>>>(Q, P);
}
```

```cpp
#include <cuda_runtime.h>
#include <cuda.h>
#include <cuda_bf16.h>
#include <stdint.h>
#include <stddef.h>
#include <string.h>
#include <math.h>

template <uint32_t HA, uint32_t HB> __device__ __forceinline__ void wg_n128(float (&d)[64], uint32_t descA, uint32_t descB, int scaleD) {
  asm volatile("{\n.reg .pred p;\n.reg .b64 da, db;\n"
    "mov.b64 da, {%64, %67};\nmov.b64 db, {%65, %68};\n"
    "setp.ne.b32 p, %66, 0;\n"
    "wgmma.mma_async.sync.aligned.m64n128k16.f32.bf16.bf16 "
    "{%0, %1, %2, %3, %4, %5, %6, %7, %8, %9, %10, %11, %12, %13, %14, %15, "
    "%16, %17, %18, %19, %20, %21, %22, %23, %24, %25, %26, %27, %28, %29, %30, %31, "
    "%32, %33, %34, %35, %36, %37, %38, %39, %40, %41, %42, %43, %44, %45, %46, %47, "
    "%48, %49, %50, %51, %52, %53, %54, %55, %56, %57, %58, %59, %60, %61, %62, %63}, "
    "da, db, p, 1, 1, 0, 1;\n}\n"
    : "+f"(d[0]), "+f"(d[1]), "+f"(d[2]), "+f"(d[3]), "+f"(d[4]), "+f"(d[5]), "+f"(d[6]), "+f"(d[7]),
      "+f"(d[8]), "+f"(d[9]), "+f"(d[10]), "+f"(d[11]), "+f"(d[12]), "+f"(d[13]), "+f"(d[14]), "+f"(d[15]),
      "+f"(d[16]), "+f"(d[17]), "+f"(d[18]), "+f"(d[19]), "+f"(d[20]), "+f"(d[21]), "+f"(d[22]), "+f"(d[23]),
      "+f"(d[24]), "+f"(d[25]), "+f"(d[26]), "+f"(d[27]), "+f"(d[28]), "+f"(d[29]), "+f"(d[30]), "+f"(d[31]),
      "+f"(d[32]), "+f"(d[33]), "+f"(d[34]), "+f"(d[35]), "+f"(d[36]), "+f"(d[37]), "+f"(d[38]), "+f"(d[39]),
      "+f"(d[40]), "+f"(d[41]), "+f"(d[42]), "+f"(d[43]), "+f"(d[44]), "+f"(d[45]), "+f"(d[46]), "+f"(d[47]),
      "+f"(d[48]), "+f"(d[49]), "+f"(d[50]), "+f"(d[51]), "+f"(d[52]), "+f"(d[53]), "+f"(d[54]), "+f"(d[55]),
      "+f"(d[56]), "+f"(d[57]), "+f"(d[58]), "+f"(d[59]), "+f"(d[60]), "+f"(d[61]), "+f"(d[62]), "+f"(d[63])
    : "r"(descA), "r"(descB), "r"(scaleD), "n"(HA), "n"(HB));
}
template <uint32_t HA, uint32_t HB> __device__ __forceinline__ void wg_n192(float (&d)[96], uint32_t descA, uint32_t descB, int scaleD) {
  asm volatile("{\n.reg .pred p;\n.reg .b64 da, db;\n"
    "mov.b64 da, {%96, %99};\nmov.b64 db, {%97, %100};\n"
    "setp.ne.b32 p, %98, 0;\n"
    "wgmma.mma_async.sync.aligned.m64n192k16.f32.bf16.bf16 "
    "{%0, %1, %2, %3, %4, %5, %6, %7, %8, %9, %10, %11, %12, %13, %14, %15, "
    "%16, %17, %18, %19, %20, %21, %22, %23, %24, %25, %26, %27, %28, %29, %30, %31, "
    "%32, %33, %34, %35, %36, %37, %38, %39, %40, %41, %42, %43, %44, %45, %46, %47, "
    "%48, %49, %50, %51, %52, %53, %54, %55, %56, %57, %58, %59, %60, %61, %62, %63, "
    "%64, %65, %66, %67, %68, %69, %70, %71, %72, %73, %74, %75, %76, %77, %78, %79, "
    "%80, %81, %82, %83, %84, %85, %86, %87, %88, %89, %90, %91, %92, %93, %94, %95}, "
    "da, db, p, 1, 1, 0, 1;\n}\n"
    : "+f"(d[0]), "+f"(d[1]), "+f"(d[2]), "+f"(d[3]), "+f"(d[4]), "+f"(d[5]), "+f"(d[6]), "+f"(d[7]),
      "+f"(d[8]), "+f"(d[9]), "+f"(d[10]), "+f"(d[11]), "+f"(d[12]), "+f"(d[13]), "+f"(d[14]), "+f"(d[15]),
      "+f"(d[16]), "+f"(d[17]), "+f"(d[18]), "+f"(d[19]), "+f"(d[20]), "+f"(d[21]), "+f"(d[22]), "+f"(d[23]),
      "+f"(d[24]), "+f"(d[25]), "+f"(d[26]), "+f"(d[27]), "+f"(d[28]), "+f"(d[29]), "+f"(d[30]), "+f"(d[31]),
      "+f"(d[32]), "+f"(d[33]), "+f"(d[34]), "+f"(d[35]), "+f"(d[36]), "+f"(d[37]), "+f"(d[38]), "+f"(d[39]),
      "+f"(d[40]), "+f"(d[41]), "+f"(d[42]), "+f"(d[43]), "+f"(d[44]), "+f"(d[45]), "+f"(d[46]), "+f"(d[47]),
      "+f"(d[48]), "+f"(d[49]), "+f"(d[50]), "+f"(d[51]), "+f"(d[52]), "+f"(d[53]), "+f"(d[54]), "+f"(d[55]),
      "+f"(d[56]), "+f"(d[57]), "+f"(d[58]), "+f"(d[59]), "+f"(d[60]), "+f"(d[61]), "+f"(d[62]), "+f"(d[63]),
      "+f"(d[64]), "+f"(d[65]), "+f"(d[66]), "+f"(d[67]), "+f"(d[68]), "+f"(d[69]), "+f"(d[70]), "+f"(d[71]),
      "+f"(d[72]), "+f"(d[73]), "+f"(d[74]), "+f"(d[75]), "+f"(d[76]), "+f"(d[77]), "+f"(d[78]), "+f"(d[79]),
      "+f"(d[80]), "+f"(d[81]), "+f"(d[82]), "+f"(d[83]), "+f"(d[84]), "+f"(d[85]), "+f"(d[86]), "+f"(d[87]),
      "+f"(d[88]), "+f"(d[89]), "+f"(d[90]), "+f"(d[91]), "+f"(d[92]), "+f"(d[93]), "+f"(d[94]), "+f"(d[95])
    : "r"(descA), "r"(descB), "r"(scaleD), "n"(HA), "n"(HB));
}
template <uint32_t HA, uint32_t HB> __device__ __forceinline__ void wg_n256(float (&d)[128], uint32_t descA, uint32_t descB, int scaleD) {
  asm volatile("{\n.reg .pred p;\n.reg .b64 da, db;\n"
    "mov.b64 da, {%128, %131};\nmov.b64 db, {%129, %132};\n"
    "setp.ne.b32 p, %130, 0;\n"
    "wgmma.mma_async.sync.aligned.m64n256k16.f32.bf16.bf16 "
    "{%0, %1, %2, %3, %4, %5, %6, %7, %8, %9, %10, %11, %12, %13, %14, %15, "
    "%16, %17, %18, %19, %20, %21, %22, %23, %24, %25, %26, %27, %28, %29, %30, %31, "
    "%32, %33, %34, %35, %36, %37, %38, %39, %40, %41, %42, %43, %44, %45, %46, %47, "
    "%48, %49, %50, %51, %52, %53, %54, %55, %56, %57, %58, %59, %60, %61, %62, %63, "
    "%64, %65, %66, %67, %68, %69, %70, %71, %72, %73, %74, %75, %76, %77, %78, %79, "
    "%80, %81, %82, %83, %84, %85, %86, %87, %88, %89, %90, %91, %92, %93, %94, %95, "
    "%96, %97, %98, %99, %100, %101, %102, %103, %104, %105, %106, %107, %108, %109, %110, %111, "
    "%112, %113, %114, %115, %116, %117, %118, %119, %120, %121, %122, %123, %124, %125, %126, %127}, "
    "da, db, p, 1, 1, 0, 1;\n}\n"
    : "+f"(d[0]), "+f"(d[1]), "+f"(d[2]), "+f"(d[3]), "+f"(d[4]), "+f"(d[5]), "+f"(d[6]), "+f"(d[7]),
      "+f"(d[8]), "+f"(d[9]), "+f"(d[10]), "+f"(d[11]), "+f"(d[12]), "+f"(d[13]), "+f"(d[14]), "+f"(d[15]),
      "+f"(d[16]), "+f"(d[17]), "+f"(d[18]), "+f"(d[19]), "+f"(d[20]), "+f"(d[21]), "+f"(d[22]), "+f"(d[23]),
      "+f"(d[24]), "+f"(d[25]), "+f"(d[26]), "+f"(d[27]), "+f"(d[28]), "+f"(d[29]), "+f"(d[30]), "+f"(d[31]),
      "+f"(d[32]), "+f"(d[33]), "+f"(d[34]), "+f"(d[35]), "+f"(d[36]), "+f"(d[37]), "+f"(d[38]), "+f"(d[39]),
      "+f"(d[40]), "+f"(d[41]), "+f"(d[42]), "+f"(d[43]), "+f"(d[44]), "+f"(d[45]), "+f"(d[46]), "+f"(d[47]),
      "+f"(d[48]), "+f"(d[49]), "+f"(d[50]), "+f"(d[51]), "+f"(d[52]), "+f"(d[53]), "+f"(d[54]), "+f"(d[55]),
      "+f"(d[56]), "+f"(d[57]), "+f"(d[58]), "+f"(d[59]), "+f"(d[60]), "+f"(d[61]), "+f"(d[62]), "+f"(d[63]),
      "+f"(d[64]), "+f"(d[65]), "+f"(d[66]), "+f"(d[67]), "+f"(d[68]), "+f"(d[69]), "+f"(d[70]), "+f"(d[71]),
      "+f"(d[72]), "+f"(d[73]), "+f"(d[74]), "+f"(d[75]), "+f"(d[76]), "+f"(d[77]), "+f"(d[78]), "+f"(d[79]),
      "+f"(d[80]), "+f"(d[81]), "+f"(d[82]), "+f"(d[83]), "+f"(d[84]), "+f"(d[85]), "+f"(d[86]), "+f"(d[87]),
      "+f"(d[88]), "+f"(d[89]), "+f"(d[90]), "+f"(d[91]), "+f"(d[92]), "+f"(d[93]), "+f"(d[94]), "+f"(d[95]),
      "+f"(d[96]), "+f"(d[97]), "+f"(d[98]), "+f"(d[99]), "+f"(d[100]), "+f"(d[101]), "+f"(d[102]), "+f"(d[103]),
      "+f"(d[104]), "+f"(d[105]), "+f"(d[106]), "+f"(d[107]), "+f"(d[108]), "+f"(d[109]), "+f"(d[110]), "+f"(d[111]),
      "+f"(d[112]), "+f"(d[113]), "+f"(d[114]), "+f"(d[115]), "+f"(d[116]), "+f"(d[117]), "+f"(d[118]), "+f"(d[119]),
      "+f"(d[120]), "+f"(d[121]), "+f"(d[122]), "+f"(d[123]), "+f"(d[124]), "+f"(d[125]), "+f"(d[126]), "+f"(d[127])
    : "r"(descA), "r"(descB), "r"(scaleD), "n"(HA), "n"(HB));
}

namespace {

constexpr int S_ = 2048, D_ = 1024, F_ = 3584;
constexpr int NCTA = 128;
constexpr int NTHREADS = 384;

constexpr uint32_t W_OFF      = 6 * 16384;
constexpr uint32_t BAR_OFF    = W_OFF + 16 * 8192;
constexpr uint32_t PAR_OFF    = BAR_OFF + 1280;
constexpr uint32_t SMEM_BYTES = 232448, SMEM_BASE = 1024;
constexpr uint32_t SL_OFF     = W_OFF + 11 * 8192;
constexpr uint32_t TAB_OFF    = W_OFF + 15 * 8192;
constexpr uint32_t B_R = 1024, B_PAR = 1072, B_SL = 1120, B_SLE = 1088, B_Q = 1096, B_ST = 1152, B_GB = 1056, B_XB = 1168, B_END = 1184, ROLE_OFF = 1272;

constexpr uint32_t H128 = 0x40000040u;
constexpr uint32_t H64  = 0x80000020u;

constexpr int N_W = 137, N_HK = 3, N_END = 130, N_PEEL = 3;
__constant__ uint2 c_cons[2][135] = {
  {
    {0x0,0x84580800}, {0x6000400,0x84580808}, {0x18000800,0x84580810}, {0x12000c00,0x84580818}, {0xc001000,0x84580820}, {0x0,0x84580828},
    {0x6000400,0x84580830}, {0x18000800,0x84580838}, {0x12000c00,0x84580840}, {0xc000000,0x84580848}, {0x800,0x84580850}, {0x6000c00,0x84580858},
    {0x18000000,0x84580860}, {0x12000800,0x84580868}, {0xc000c00,0x84580870}, {0x0,0x84580878}, {0x400,0x84580880}, {0x400,0x84580888},
    {0x18001000,0x4500890}, {0x1c000000,0x84580898}, {0x14000800,0x845818a0}, {0xc001400,0x41008a8}, {0x10000c00,0x845818b0}, {0x1000,0x41808b8},
    {0x4000000,0x845808c0}, {0x8000800,0x845808c8}, {0x1400,0x845808d0}, {0x1400,0x845808d8}, {0x18000000,0x3b808e0}, {0xc000800,0x845808e8},
    {0x12001400,0x845808f0}, {0xc00,0x845808f8}, {0x6001000,0x84580c00}, {0x18000400,0x84580c08}, {0xc000000,0x84580c10}, {0x12000800,0x84580c18},
    {0xc00,0x84580c20}, {0x6000400,0x84580c28}, {0x18000800,0x84580c30}, {0xc000c00,0x84580c38}, {0x12000400,0x84580c40}, {0x800,0x84580c48},
    {0x6000c00,0x84580c50}, {0x18000400,0x84580c58}, {0x0,0x3d80c60}, {0x14001400,0x83500c68}, {0xc00,0x84580c70}, {0x4001000,0x84580c78},
    {0x8000400,0x84580c80}, {0x18000000,0x84580c88}, {0xc000800,0x84580c90}, {0x10000c00,0x84580c98}, {0x1c000400,0x84580ca0}, {0x14000800,0x84580ca8},
    {0xc00,0x84580cb0}, {0x4000400,0x84580cb8}, {0x8000800,0x84580cc0}, {0x18000c00,0x84580cc8}, {0xc000400,0x84580cd0}, {0x10000800,0x84580cd8},
    {0x1c000c00,0x84580ce0}, {0x14001000,0x83d80ce8}, {0x400,0x84580cf0}, {0x4000000,0x84580cf8}, {0x8000800,0x84580800}, {0x18001400,0x84580808},
    {0xc000c00,0x84580810}, {0x10000400,0x84580818}, {0x1c000800,0x84580820}, {0x14000c00,0x84580828}, {0x400,0x84580830}, {0x4000800,0x84580838},
    {0x8000c00,0x84580840}, {0x18000400,0x84580848}, {0xc000800,0x84580850}, {0x10000c00,0x84580858}, {0x1c000400,0x84580860}, {0x14000000,0x3580868},
    {0x800,0x84580870}, {0x4001400,0x84580878}, {0x8000c00,0x84580880}, {0x18001000,0x84580888}, {0xc000400,0x84580890}, {0x10000000,0x84580898},
    {0x1c000800,0x845808a0}, {0x14001400,0x845808a8}, {0xc00,0x845808b0}, {0x4001000,0x845808b8}, {0x8000400,0x845808c0}, {0x18000000,0x845808c8},
    {0xc000800,0x845808d0}, {0x10001400,0x845808d8}, {0x1c000c00,0x845808e0}, {0x14001000,0x845808e8}, {0x400,0x845808f0}, {0x4000000,0x845808f8},
    {0x8000800,0x84580c00}, {0x18001400,0x84580c08}, {0xc000c00,0x84580c10}, {0x10001000,0x84580c18}, {0x1c000400,0x84580c20}, {0x14000000,0x84580c28},
    {0x800,0x84580c30}, {0x4001400,0x84580c38}, {0x8000c00,0x84580c40}, {0x18001000,0x84580c48}, {0xc000400,0x84580c50}, {0x10000000,0x84580c58},
    {0x1c000800,0x84580c60}, {0x14001400,0x84580c68}, {0xc00,0x84580c70}, {0x4001000,0x84580c78}, {0x8000400,0x84580c80}, {0x18000000,0x84580c88},
    {0xc000800,0x84580c90}, {0x10001400,0x84580c98}, {0x1c000c00,0x84580ca0}, {0x14001000,0x84580ca8}, {0x400,0x84580cb0}, {0x4000000,0x84580cb8},
    {0x8000800,0x84580cc0}, {0x18001400,0x84580cc8}, {0xc000c00,0x84580cd0}, {0x10001000,0x84580cd8}, {0x1c000400,0x84580ce0}, {0x14000000,0x84580ce8},
    {0x800,0x84580cf0}, {0x4001400,0x845804f8}, {0x8000c00,0x84580000}, {0x18001000,0x84580008}, {0x400,0x84580010}, {0x0,0x84580018},
    {0x14000800,0x0}, {0x14000800,0x0}, {0x14000800,0x0},
  },
  {
    {0x6001400,0x300900}, {0x18001000,0x380908}, {0x12000400,0x400910}, {0xc001400,0x480918}, {0x1000,0x500920}, {0x6000400,0x580928},
    {0x18001400,0x600930}, {0x12001000,0x680938}, {0xc000800,0x4480940}, {0x1400,0x84581948}, {0x6000c00,0x4001950}, {0x18001000,0x4080958},
    {0x12000000,0x84580960}, {0xc000800,0x84580968}, {0x1400,0x84580970}, {0x6000c00,0x84580978}, {0x400,0x84580980}, {0x400,0x84580988},
    {0x18000c00,0x2b80990}, {0x1c001000,0x84580998}, {0x14000400,0x845809a0}, {0xc000000,0x845809a8}, {0x10000800,0x845809b0}, {0x1400,0x845809b8},
    {0x4000c00,0xc009c0}, {0x8001000,0xc809c8}, {0x400,0x845809d0}, {0x400,0x845809d8}, {0xc001400,0x801009e0}, {0x12001000,0x801809e8},
    {0x0,0x802009f0}, {0x6001400,0x802809f8}, {0x18001000,0x80300d00}, {0xc000000,0x80380d08}, {0x12001400,0x80400d10}, {0x1000,0x80480d18},
    {0x6000000,0x82500d20}, {0x18000800,0x80580d28}, {0xc001400,0x84580d30}, {0x12000c00,0x84580d38}, {0x1000,0x84580d40}, {0x6000400,0x84580d48},
    {0x18000000,0x84580d50}, {0xc000800,0x84580d58}, {0x0,0x82600d60}, {0x14001400,0x82680d68}, {0x1000,0x82700d70}, {0x4000000,0x82780d78},
    {0x8001400,0x82800d80}, {0x18001000,0x82880d88}, {0xc000000,0x82900d90}, {0x10001400,0x82980d98}, {0x1c001000,0x82a00da0}, {0x14000000,0x82a80da8},
    {0x1400,0x82b00db0}, {0x4001000,0x82d80db8}, {0x8000400,0x84580dc0}, {0x18000000,0x84580dc8}, {0xc000800,0x84580dd0}, {0x10001400,0x84580dd8},
    {0x1c000c00,0x82e00de0}, {0x14001000,0x82e80de8}, {0x0,0x82f00df0}, {0x4001400,0x82f80df8}, {0x8001000,0x2000900}, {0x18000000,0x2080908},
    {0xc001400,0x2100910}, {0x10001000,0x2180918}, {0x1c000000,0x2200920}, {0x14001400,0x2280928}, {0x1000,0x2300930}, {0x4000000,0x2580938},
    {0x8000800,0x84580940}, {0x18001400,0x84580948}, {0xc000c00,0x84580950}, {0x10001000,0x84580958}, {0x1c000400,0x2600960}, {0x14000000,0x2680968},
    {0x800,0x2700970}, {0x4001400,0x2780978}, {0x8000c00,0x2800980}, {0x18001000,0x2880988}, {0xc000400,0x2900990}, {0x10000000,0x2980998},
    {0x1c000800,0x2a009a0}, {0x14001400,0x2a809a8}, {0xc00,0x2b009b0}, {0x4001000,0x2b809b8}, {0x8000400,0x2c009c0}, {0x18000000,0x2c809c8},
    {0xc000800,0x2d009d0}, {0x10001400,0x2d809d8}, {0x1c000c00,0x2e009e0}, {0x14001000,0x2e809e8}, {0x400,0x2f009f0}, {0x4000000,0x2f809f8},
    {0x8000800,0x82000d00}, {0x18001400,0x82080d08}, {0xc000c00,0x82100d10}, {0x10001000,0x82180d18}, {0x1c000400,0x82200d20}, {0x14000000,0x82280d28},
    {0x800,0x82300d30}, {0x4001400,0x82380d38}, {0x8000c00,0x82400d40}, {0x18001000,0x82480d48}, {0xc000400,0x82500d50}, {0x10000000,0x82580d58},
    {0x1c000800,0x82600d60}, {0x14001400,0x82680d68}, {0xc00,0x82700d70}, {0x4001000,0x82780d78}, {0x8000400,0x82800d80}, {0x18000000,0x82880d88},
    {0xc000800,0x82900d90}, {0x10001400,0x82980d98}, {0x1c000c00,0x82a00da0}, {0x14001000,0x82a80da8}, {0x400,0x82b00db0}, {0x4000000,0x82b80db8},
    {0x8000800,0x82c00dc0}, {0x18001400,0x82c80dc8}, {0xc000c00,0x82d00dd0}, {0x10001000,0x82d80dd8}, {0x1c000400,0x82e00de0}, {0x14000000,0x82e80de8},
    {0x800,0x82f005f0}, {0x4001400,0x80f805f8}, {0x8000c00,0x100}, {0x18001000,0x80108}, {0x400,0x84580110}, {0x0,0x84580118},
    {0x14000800,0x0}, {0x14000800,0x0}, {0x14000800,0x0},
  },
};
__constant__ uint2 c_act[2][135] = {
  {
    {0x81000458,0xa0000000}, {0x80004458,0xa0004008}, {0x80008458,0xa0008010}, {0x8000c458,0xa000c018}, {0x80010458,0xa0010020}, {0x14200,0xa0000028},
    {0x18208,0xa0004030}, {0x1c210,0xa0008038}, {0x3020218,0xa000c040}, {0x24228,0xa0000048}, {0x28238,0xa0008050}, {0x2c240,0xa000c058},
    {0x30248,0xa0000060}, {0x34250,0xa0008068}, {0x38258,0xa000c070}, {0x3c260,0xa0000078}, {0x328,0x4080}, {0x280,0x40004088},
    {0x5100358,0x80010090}, {0x108360,0x80000098}, {0x110368,0x800080a0}, {0x118370,0x800140a8}, {0x120378,0x8000c0b0}, {0x128290,0x800100b8},
    {0x130298,0x800000c0}, {0x1382a0,0x800080c8}, {0x2a8,0x140d0}, {0x80000458,0x400140d8}, {0x70003a8,0xa00000e0}, {0x43b0,0xa00080e8},
    {0x83b8,0xa00140f0}, {0xc3c0,0xa000c0f8}, {0x103c8,0xa0010000}, {0x143d8,0xa0004008}, {0x182e0,0xa0000010}, {0x1c2e8,0xa0008018},
    {0x202f8,0xa000c020}, {0x80024208,0xa0004028}, {0x80028218,0xa0008030}, {0x8002c220,0xa000c038}, {0x80030228,0xa0004040}, {0x80034230,0xa0008048},
    {0x80038238,0xa000c050}, {0x8003c240,0xa0004058}, {0x80000458,0x20000060}, {0x80000330,0x80014068}, {0x80004338,0x8000c070}, {0x80008340,0x80010078},
    {0x8000c348,0x80004080}, {0x80010350,0x80000088}, {0x80014358,0x80008090}, {0x80018270,0x8000c098}, {0x8001c280,0x800040a0}, {0x80020290,0x800080a8},
    {0x80024298,0x8000c0b0}, {0x800282a0,0x800040b8}, {0x8002c2a8,0x800080c0}, {0x800302b0,0x8000c0c8}, {0x800342b8,0x800040d0}, {0x800382c0,0x800080d8},
    {0x8003c2c8,0x8000c0e0}, {0x800003b8,0x800100e8}, {0x800043c0,0x800040f0}, {0x800083c8,0x800000f8}, {0x8000c3d0,0x80008000}, {0x800103d8,0x80014008},
    {0x800143e0,0x8000c010}, {0x800182f0,0x80004018}, {0x1c200,0x80008020}, {0x20210,0x8000c028}, {0x24218,0x80004030}, {0x28220,0x80008038},
    {0x2c228,0x8000c040}, {0x30230,0x80004048}, {0x34238,0x80008050}, {0x38240,0x8000c058}, {0x3c248,0x80004060}, {0x910c338,0x60000068},
    {0x110340,0x60008070}, {0x114348,0x60014078}, {0x118350,0x6000c080}, {0x11c358,0x60010088}, {0x120360,0x60004090}, {0x124268,0x60000098},
    {0x128270,0x600080a0}, {0x12c278,0x600140a8}, {0x130280,0x6000c0b0}, {0x134288,0x600100b8}, {0x138290,0x600040c0}, {0x13c298,0x600000c8},
    {0x1402a0,0x600080d0}, {0x1442a8,0x600140d8}, {0x1482b0,0x6000c0e0}, {0x14c2b8,0x600100e8}, {0x1502c0,0x600040f0}, {0x1542c8,0x600000f8},
    {0x1582d0,0x60008000}, {0x15c2d8,0x60014008}, {0xb1602e0,0x6000c010}, {0x1642e8,0x60010018}, {0x1682f0,0x60004020}, {0x16c2f8,0x60000028},
    {0x80170200,0x60008030}, {0x80174208,0x60014038}, {0x80178210,0x6000c040}, {0x8017c218,0x60010048}, {0x80180220,0x60004050}, {0x80184228,0x60000058},
    {0x80188230,0x60008060}, {0x8018c238,0x60014068}, {0x80190240,0x6000c070}, {0x80194248,0x60010078}, {0x80198250,0x60004080}, {0x8019c258,0x60000088},
    {0x8d1a0260,0x60008090}, {0x801a4268,0x60014098}, {0x801a8270,0x6000c0a0}, {0x801ac278,0x600100a8}, {0x801b0280,0x600040b0}, {0x801b4288,0x600000b8},
    {0x801b8290,0x600080c0}, {0x801bc298,0x600140c8}, {0x801c02a0,0x6000c0d0}, {0x801c42a8,0x600100d8}, {0x801c82b0,0x600040e0}, {0x801cc2b8,0x600000e8},
    {0x801d02c0,0x600080f0}, {0x801d42c8,0x600140f8}, {0x801d82d0,0x6000c000}, {0x801dc2d8,0x60010008}, {0x800802e0,0x20004010}, {0x800842e8,0x20000018},
    {0x0,0x0}, {0x0,0x0}, {0x0,0x0},
  },
  {
    {0x91058458,0x40014100}, {0x5c220,0x40010108}, {0x60230,0x40004110}, {0x64300,0x40014118}, {0x68308,0x40010120}, {0x6c310,0x40004128},
    {0x70318,0x40014130}, {0x74320,0x40010138}, {0x78268,0x40008140}, {0x7c330,0x40014148}, {0x40270,0xa000c150}, {0x44338,0xa0010158},
    {0x48278,0xa0000160}, {0x4c340,0xa0008168}, {0x50348,0xa0014170}, {0x54350,0xa000c178}, {0x288,0x4180}, {0x380,0x40004188},
    {0x151e02b0,0x4000c190}, {0x1e82b8,0x40010198}, {0x1f0388,0x400041a0}, {0x1f82c0,0x400001a8}, {0x2002c8,0x400081b0}, {0x2082d8,0x400141b8},
    {0x210390,0x4000c1c0}, {0x218398,0x400101c8}, {0x3a0,0x41d0}, {0x80000458,0x400041d8}, {0x170582f0,0x400141e0}, {0x8005c200,0x400101e8},
    {0x80060210,0x400001f0}, {0x643e0,0x400141f8}, {0x683e8,0x40010100}, {0x6c3f0,0x40000108}, {0x703f8,0x40014110}, {0x80074300,0x40010118},
    {0x80078308,0x40000120}, {0x8007c248,0x40008128}, {0x80040310,0xa0014130}, {0x80044250,0xa000c138}, {0x80048318,0xa0010140}, {0x8004c258,0xa0004148},
    {0x80050320,0xa0000150}, {0x80054328,0xa0008158}, {0x80000458,0x20000160}, {0x80040268,0x40014168}, {0x80044278,0x40010170}, {0x80048288,0x40000178},
    {0x8004c368,0x40014180}, {0x80050370,0x40010188}, {0x80054378,0x40000190}, {0x80058380,0x40014198}, {0x8005c388,0x400101a0}, {0x80060390,0x400001a8},
    {0x80064398,0x400141b0}, {0x800683a0,0x400101b8}, {0x8006c2d0,0x400041c0}, {0x800703a8,0x400001c8}, {0x800742d8,0x400081d0}, {0x800783b0,0x400141d8},
    {0x8007c2e0,0x4000c1e0}, {0x800402e8,0x400101e8}, {0x800442f8,0x400001f0}, {0x48208,0x400141f8}, {0x8004c3e8,0x40010100}, {0x800503f0,0x40000108},
    {0x800543f8,0x40014110}, {0x58300,0x40010118}, {0x5c308,0x40000120}, {0x60310,0x40014128}, {0x64318,0x40010130}, {0x68320,0x40000138},
    {0x6c250,0x40008140}, {0x70328,0x40014148}, {0x74258,0x4000c150}, {0x78330,0x40010158}, {0x7c260,0x40004160}, {0x910c338,0x20000168},
    {0x110340,0x20008170}, {0x114348,0x20014178}, {0x118350,0x2000c180}, {0x11c358,0x20010188}, {0x120360,0x20004190}, {0x124368,0x20000198},
    {0x128370,0x200081a0}, {0x12c378,0x200141a8}, {0x130380,0x2000c1b0}, {0x134388,0x200101b8}, {0x138390,0x200041c0}, {0x13c398,0x200001c8},
    {0x1403a0,0x200081d0}, {0x1443a8,0x200141d8}, {0x1483b0,0x2000c1e0}, {0x14c3b8,0x200101e8}, {0x1503c0,0x200041f0}, {0x1543c8,0x200001f8},
    {0x1583d0,0x20008100}, {0x15c3d8,0x20014108}, {0xb1603e0,0x2000c110}, {0x1643e8,0x20010118}, {0x1683f0,0x20004120}, {0x16c3f8,0x20000128},
    {0x80170300,0x20008130}, {0x80174308,0x20014138}, {0x80178310,0x2000c140}, {0x8017c318,0x20010148}, {0x80180320,0x20004150}, {0x80184328,0x20000158},
    {0x80188330,0x20008160}, {0x8018c338,0x20014168}, {0x80190340,0x2000c170}, {0x80194348,0x20010178}, {0x80198350,0x20004180}, {0x8019c358,0x20000188},
    {0x8d1a0360,0x20008190}, {0x801a4368,0x20014198}, {0x801a8370,0x2000c1a0}, {0x801ac378,0x200101a8}, {0x801b0380,0x200041b0}, {0x801b4388,0x200001b8},
    {0x801b8390,0x200081c0}, {0x801bc398,0x200141c8}, {0x801c03a0,0x2000c1d0}, {0x801c43a8,0x200101d8}, {0x801c83b0,0x200041e0}, {0x801cc3b8,0x200001e8},
    {0x801d03c0,0x200081f0}, {0x801d43c8,0x200141f8}, {0x801d83d0,0x2000c100}, {0x801dc3d8,0x20010108}, {0x800803e0,0x20004110}, {0x800843e8,0x20000118},
    {0x0,0x0}, {0x0,0x0}, {0x0,0x0},
  },
};
__constant__ uint2 c_w[1][138] = {
  {
    {0x84580000,0x20000}, {0x84580000,0x2026008}, {0x84580000,0x4038010}, {0x84580000,0x6032018}, {0x84580000,0x802c020}, {0x2000000,0xa000028},
    {0x2080000,0xc006030}, {0x2100000,0xe018038}, {0x2180000,0x10012040}, {0x2200000,0x1200c048}, {0x2280000,0x14000050}, {0x2300300,0x16006058},
    {0x2380308,0x18018060}, {0x2400310,0x1a012068}, {0x2480318,0x1c00c070}, {0x2500320,0x1e000078}, {0x2580328,0x6150}, {0x2600330,0x2018158},
    {0x2680338,0x4012160}, {0x2700340,0x600c168}, {0x2780348,0x8000170}, {0x3500000,0xa026178}, {0x3580000,0x18890}, {0x84580000,0x401c898},
    {0x3600000,0x80148a0}, {0x3680000,0xc00c8a8}, {0x84580000,0x100108b0}, {0x3700000,0x140008b8}, {0x3780000,0x180048c0}, {0x84580000,0x1c0288c8},
    {0x3980000,0x184e0}, {0x3b00000,0x200c4e8}, {0x84580000,0x40124f0}, {0x2c003c0,0x60004f8}, {0x2c803c8,0x8006400}, {0x2e00000,0xa018408},
    {0x2e80000,0xc00c410}, {0x2f00000,0xe012418}, {0x2f80000,0x10000420}, {0x82000000,0x12006428}, {0x82080000,0x14018430}, {0x821003e0,0x1600c438},
    {0x821803e8,0x18012440}, {0x822003f0,0x1a000448}, {0x822803f8,0x1c006450}, {0x82308300,0x1e018458}, {0x82388308,0xc530}, {0x82408310,0x2012538},
    {0x82488318,0x4000540}, {0x83200000,0x6006548}, {0x82588328,0x8018550}, {0x83300000,0xa02c558}, {0x83380000,0x14c68}, {0x83400000,0x2000c70},
    {0x83480000,0x4004c78}, {0x84580000,0x6008c80}, {0x83500000,0x8018c88}, {0x83580000,0xa00cc90}, {0x84580000,0xc010c98}, {0x83600000,0xe01cca0},
    {0x83680000,0x10014ca8}, {0x83700000,0x12000cb0}, {0x83780000,0x14004cb8}, {0x83800000,0x16008cc0}, {0x83880000,0x18018cc8}, {0x83900000,0x1a00ccd0},
    {0x83980000,0x1c010cd8}, {0x83a00000,0x1e03cce0}, {0x83a80000,0x150e8}, {0x83b00000,0x20010f0}, {0x83b80000,0x40050f8}, {0x83c00000,0x6009000},
    {0x83c80000,0x8019008}, {0x83d00000,0xa00d010}, {0x83d80000,0xc011018}, {0x83e00000,0xe01d020}, {0x83e80000,0x10015028}, {0x83f00000,0x12001030},
    {0x83f80000,0x14005038}, {0x3000000,0x16009040}, {0x3080000,0x18019048}, {0x3100000,0x1a00d050}, {0x3180000,0x1c011058}, {0x3200000,0x1e03d060},
    {0x3280000,0x6015468}, {0x3300000,0x8001470}, {0x3380000,0xa005478}, {0x3400000,0xc009480}, {0x3480000,0xe019488}, {0x3500000,0x1000d490},
    {0x3580000,0x12011498}, {0x3600000,0x1401d4a0}, {0x3680000,0x160154a8}, {0x3700000,0x180014b0}, {0x3780000,0x1a0054b8}, {0x3800000,0x1c0094c0},
    {0x3880000,0x1e0194c8}, {0x3900000,0x2000d4d0}, {0x3980000,0x220114d8}, {0x3a00000,0x2401d4e0}, {0x3a80000,0x260154e8}, {0x3b00000,0x280014f0},
    {0x3b80000,0x2a0054f8}, {0x3c00000,0x2c009400}, {0x3c80000,0x2e019408}, {0x3d00000,0x3000d410}, {0x3d80000,0x32011418}, {0x3e00000,0x3401d420},
    {0x3e80000,0x36015428}, {0x3f00000,0x38001430}, {0x3f80000,0x3a005438}, {0x83000000,0x3c009440}, {0x83080000,0x3e019448}, {0x83100000,0x4000d450},
    {0x83180000,0x42011458}, {0x83200000,0x4401d460}, {0x83280000,0x46015468}, {0x83300000,0x48001470}, {0x83380000,0x4a005478}, {0x83400000,0x4c009480},
    {0x83480000,0x4e019488}, {0x83500000,0x5000d490}, {0x83580000,0x52011498}, {0x83600000,0x5401d4a0}, {0x83680000,0x560154a8}, {0x83700000,0x580014b0},
    {0x83780000,0x5a0054b8}, {0x83800000,0x5c0094c0}, {0x83880000,0x5e0194c8}, {0x83900000,0x6000d4d0}, {0x83980000,0x620114d8}, {0x83a00000,0x6401d4e0},
    {0x83a80000,0x660154e8}, {0x83b00000,0x680014f0}, {0x83b80000,0x6a0054f8}, {0x83c00000,0x6c009400}, {0x83c80000,0x6e039408}, {0x0,0x0},
  },
};

constexpr int T_H = 0, T_X1 = 32, T_ACT = 64, N_TILES = 176;
constexpr int G_H0 = 0, G_H1 = 1, G_O = 2, G_H2 = 3, G_ACT = 4, G_X1 = 7, G_HK = 15;

struct Scratch {
  uint4 img[8 * N_TILES * 1024];
  uint32_t mod0[4 * 4 * 512];
  uint32_t modp[4096];
  uint2 stat[32 * 8 * 64];
  uint4 halo[16 * 16 * 128];
  uint32_t cnt[8 * 32];
  uint32_t ep[(NCTA + 4) * 32];
};
__device__ __align__(1024) Scratch g_s;

struct Ptrs {
  const __nv_bfloat16 *x, *c;
  Scratch* s;
  __nv_bfloat16* out;
};
struct Params {
  CUtensorMap mWqkv, mWo, mWg, mWu, mWd, mOut, mWm2, mX;
};

__device__ __forceinline__ uint32_t smem_u32(const void* p) { return (uint32_t)__cvta_generic_to_shared(p); }
__device__ __forceinline__ void mbar_init(uint32_t bar, uint32_t cnt) { asm volatile("mbarrier.init.shared::cta.b64 [%0], %1;" ::"r"(bar), "r"(cnt)); }
__device__ __forceinline__ void mbar_expect_tx(uint32_t bar, uint32_t bytes) { asm volatile("mbarrier.arrive.expect_tx.shared::cta.b64 _, [%0], %1;" ::"r"(bar), "r"(bytes) : "memory"); }
__device__ __forceinline__ void mbar_arrive(uint32_t bar) { asm volatile("mbarrier.arrive.shared::cta.b64 _, [%0];" ::"r"(bar) : "memory"); }
__device__ __forceinline__ void mbar_arrive_remote(uint32_t bar_cluster) { asm volatile("mbarrier.arrive.shared::cluster.b64 _, [%0];" ::"r"(bar_cluster) : "memory"); }
__device__ __forceinline__ uint32_t mapa(uint32_t a, uint32_t cta) { uint32_t r; asm volatile("mapa.shared::cluster.u32 %0, %1, %2;" : "=r"(r) : "r"(a), "r"(cta)); return r; }
__device__ __forceinline__ void mbar_wait(uint32_t bar, uint32_t parity) {
  asm volatile("{\n.reg .pred p;\nW: mbarrier.try_wait.parity.shared::cta.b64 p, [%0], %1;\n@!p bra W;\n}" ::"r"(bar), "r"(parity) : "memory");
}
__device__ __forceinline__ void mbar_wait_bounded(uint32_t bar, uint32_t parity) {
  asm volatile("{\n.reg .pred p;\n.reg .u32 c;\nmov.u32 c, 0;\n"
               "W: mbarrier.try_wait.parity.shared::cta.b64 p, [%0], %1;\n@p bra D;\n"
               "add.u32 c, c, 1;\nsetp.lt.u32 p, c, 0x200000;\n@p bra W;\ntrap;\nD:\n}" ::"r"(bar), "r"(parity) : "memory");
}
constexpr uint32_t POLL_MAX = 1u << 20;
__device__ __forceinline__ void guard(uint32_t it) { asm volatile("{\n.reg .pred p;\nsetp.gt.u32 p, %0, 0x100000;\n@p trap;\n}" ::"r"(it)); }
__device__ __forceinline__ bool mbar_test(uint32_t bar, uint32_t parity) {
  uint32_t p; asm volatile("{\n.reg .pred P;\nmbarrier.test_wait.parity.shared::cta.b64 P, [%1], %2;\nselp.u32 %0, 1, 0, P;\n}" : "=r"(p) : "r"(bar), "r"(parity) : "memory"); return p;
}
__device__ __forceinline__ bool elect_one() {
  uint32_t p; asm volatile("{\n.reg .pred P;\nelect.sync _|P, 0xffffffff;\nselp.u32 %0, 1, 0, P;\n}" : "=r"(p)); return p;
}
__device__ __forceinline__ bool only_one() { asm volatile("{\n.reg .pred P;\nelect.sync _|P, 0xffffffff;\n@!P exit;\n}" ::: "memory"); return true; }
__device__ __forceinline__ void tma2d(uint32_t dst, const CUtensorMap* m, uint32_t bar, int c0, int c1) {
  asm volatile("cp.async.bulk.tensor.2d.shared::cluster.global.mbarrier::complete_tx::bytes [%0], [%1, {%3, %4}], [%2];" ::"r"(dst), "l"(m), "r"(bar), "r"(c0), "r"(c1) : "memory");
}
__device__ __forceinline__ uint64_t evict_first() { uint64_t p; asm("createpolicy.fractional.L2::evict_first.b64 %0, 1.0;" : "=l"(p)); return p; }
__device__ __forceinline__ void tma2d_once(uint32_t dst, const CUtensorMap* m, uint32_t bar, int c0, int c1) {
  asm volatile("cp.async.bulk.tensor.2d.shared::cluster.global.mbarrier::complete_tx::bytes.L2::cache_hint [%0], [%1, {%3, %4}], [%2], %5;" ::"r"(dst), "l"(m), "r"(bar), "r"(c0), "r"(c1), "l"(evict_first()) : "memory");
}
__device__ __forceinline__ void tma5d_once(uint32_t dst, const CUtensorMap* m, uint32_t bar, int c0, int c4) {
  asm volatile("cp.async.bulk.tensor.5d.shared::cluster.global.mbarrier::complete_tx::bytes.L2::cache_hint [%0], [%1, {%3, %5, %5, %5, %4}], [%2], %6;" ::"r"(dst), "l"(m), "r"(bar), "r"(c0), "r"(c4), "r"(0), "l"(evict_first()) : "memory");
}
__device__ __forceinline__ void tma5d(uint32_t dst, const CUtensorMap* m, uint32_t bar, int c0, int c4) {
  asm volatile("cp.async.bulk.tensor.5d.shared::cluster.global.mbarrier::complete_tx::bytes [%0], [%1, {%3, %5, %5, %5, %4}], [%2];" ::"r"(dst), "l"(m), "r"(bar), "r"(c0), "r"(c4), "r"(0) : "memory");
}
__device__ __forceinline__ void tma2d_st(const CUtensorMap* m, uint32_t src, int c0, int c1) {
  asm volatile("cp.async.bulk.tensor.2d.global.shared::cta.bulk_group [%0, {%2, %3}], [%1];" ::"l"(m), "r"(src), "r"(c0), "r"(c1) : "memory");
}
__device__ __forceinline__ void bulk_g2s(uint32_t dst, const void* src, uint32_t bytes, uint32_t bar) {
  asm volatile("cp.async.bulk.shared::cluster.global.mbarrier::complete_tx::bytes [%0], [%1], %2, [%3];" ::"r"(dst), "l"(src), "r"(bytes), "r"(bar) : "memory");
}
__device__ __forceinline__ void bulk_g2s_mc(uint32_t dst, const void* src, uint32_t bytes, uint32_t bar) {
  asm volatile("cp.async.bulk.shared::cluster.global.mbarrier::complete_tx::bytes.multicast::cluster [%0], [%1], %2, [%3], %4;" ::"r"(dst), "l"(src), "r"(bytes), "r"(bar), "h"((uint16_t)3) : "memory");
}
__device__ __forceinline__ void st_async(uint32_t dst, uint32_t bar, uint32_t a, uint32_t b, uint32_t c, uint32_t d) {
  asm volatile("st.async.weak.shared::cluster.mbarrier::complete_tx::bytes.v4.b32 [%0], {%2,%3,%4,%5}, [%1];" ::"r"(dst), "r"(bar), "r"(a), "r"(b), "r"(c), "r"(d) : "memory");
}
__device__ __forceinline__ void bulk_commit() { asm volatile("cp.async.bulk.commit_group;" ::: "memory"); }
__device__ __forceinline__ void bulk_wait_read() { asm volatile("cp.async.bulk.wait_group.read 0;" ::: "memory"); }
__device__ __forceinline__ void fence_async_smem() { asm volatile("fence.proxy.async.shared::cta;" ::: "memory"); }
__device__ __forceinline__ void fence_async_glob() { asm volatile("fence.proxy.async.global;" ::: "memory"); }
__device__ __forceinline__ void prefetch_tmap(const CUtensorMap* m) { asm volatile("prefetch.tensormap [%0];" ::"l"(m) : "memory"); }
__device__ __forceinline__ void wg_fence() { asm volatile("wgmma.fence.sync.aligned;" ::: "memory"); }
__device__ __forceinline__ void wg_commit() { asm volatile("wgmma.commit_group.sync.aligned;" ::: "memory"); }
template <int N> __device__ __forceinline__ void wg_wait() { asm volatile("wgmma.wait_group.sync.aligned %0;" ::"n"(N) : "memory"); }
template <int N> __device__ __forceinline__ void fence_regs(float (&a)[N]) {
#pragma unroll
  for (int i = 0; i < N; i++) asm volatile("" : "+f"(a[i])::"memory");
}
__device__ __forceinline__ uint32_t make_desc(uint32_t addr, uint32_t lbo) { return ((addr & 0x3FFFF) >> 4) | ((lbo >> 4) << 16); }
__device__ __forceinline__ void named_sync(int id, int n) { asm volatile("bar.sync %0, %1;" ::"r"(id), "r"(n) : "memory"); }
__device__ __forceinline__ uint32_t ld_relaxed(const void* p) { uint32_t v; asm volatile("ld.relaxed.gpu.global.u32 %0, [%1];" : "=r"(v) : "l"(p) : "memory"); return v; }
__device__ __forceinline__ uint32_t ld_relaxed_line(const void* p) { uint32_t v; asm volatile("ld.relaxed.gpu.global.L2::128B.u32 %0, [%1];" : "=r"(v) : "l"(p) : "memory"); return v; }
__device__ __forceinline__ void red_relaxed(uint32_t* p, uint32_t v) { asm volatile("red.relaxed.gpu.global.add.u32 [%0], %1;" ::"l"(p), "r"(v) : "memory"); }
__device__ __forceinline__ void st_relaxed(uint32_t* p, uint32_t v) { asm volatile("st.relaxed.gpu.global.u32 [%0], %1;" ::"l"(p), "r"(v) : "memory"); }
__device__ __forceinline__ uint2 ld_relaxed_b64(const uint2* p) {
  uint64_t a; asm volatile("ld.relaxed.gpu.global.b64 %0, [%1];" : "=l"(a) : "l"(p) : "memory");
  return make_uint2((uint32_t)a, (uint32_t)(a >> 32));
}
__device__ __forceinline__ void st_relaxed_b64(void* p, uint32_t lo, uint32_t hi) {
  uint64_t v = ((uint64_t)hi << 32) | lo;
  asm volatile("st.relaxed.gpu.global.b64 [%0], %1;" ::"l"(p), "l"(v) : "memory");
}
__device__ __forceinline__ void st_relaxed_v4(uint4* p, uint32_t a, uint32_t b, uint32_t c, uint32_t d) {
  asm volatile("st.relaxed.gpu.global.v4.u32 [%0], {%1,%2,%3,%4};" ::"l"(p), "r"(a), "r"(b), "r"(c), "r"(d) : "memory");
}
__device__ __forceinline__ bool empty(const uint4& v) { return v.x == ~0u || v.y == ~0u || v.z == ~0u || v.w == ~0u; }
__device__ __forceinline__ uint32_t tag_of(uint32_t ep) { return ep % 3 + 1; }
__device__ __forceinline__ uint32_t tagf(float v, uint32_t ep) {
  uint32_t r; asm volatile("lop3.b32 %0, %1, %2, 3, 0xD8;" : "=r"(r) : "r"(__float_as_uint(v)), "r"(ep)); return r;
}
__device__ __forceinline__ uint32_t tag_bad(const uint4& v, uint32_t ep) { return ((v.x ^ ep) | (v.y ^ ep) | (v.z ^ ep) | (v.w ^ ep)) & 3u; }
__device__ __forceinline__ uint4 ld_relaxed_v4(const void* p) {
  uint4 v; asm volatile("ld.relaxed.gpu.global.v4.u32 {%0,%1,%2,%3}, [%4];" : "=r"(v.x), "=r"(v.y), "=r"(v.z), "=r"(v.w) : "l"(p) : "memory"); return v;
}
__device__ __forceinline__ uint32_t ldg32(const void* p) { uint32_t v; asm volatile("ld.global.u32 %0, [%1];" : "=r"(v) : "l"(p) : "memory"); return v; }
__device__ __forceinline__ void stg128(uint4* p, uint32_t a, uint32_t b, uint32_t c, uint32_t d) {
  asm volatile("st.global.v4.b32 [%0], {%1,%2,%3,%4};" ::"l"(p), "r"(a), "r"(b), "r"(c), "r"(d) : "memory");
}
__device__ __forceinline__ void landed(uint32_t v) { if (__all_sync(~0u, v == 0xffffffffu)) __nanosleep(1); }
__device__ __forceinline__ void publish(uint32_t seen, uint32_t* cnt, uint32_t inc) {
  landed(seen);
  if (elect_one()) red_relaxed(cnt, inc);
}
__device__ __forceinline__ uint32_t pack_bf16(float lo, float hi) { uint32_t r; asm("cvt.rn.bf16x2.f32 %0, %1, %2;" : "=r"(r) : "f"(hi), "f"(lo)); return r; }
__device__ __forceinline__ float bf_lo(uint32_t v) { return __uint_as_float(v << 16); }
__device__ __forceinline__ float bf_hi(uint32_t v) { return __uint_as_float(v & 0xffff0000u); }
__device__ __forceinline__ uint32_t hmul2_bf16(uint32_t a, uint32_t b) { uint32_t r; asm("mul.rn.bf16x2 %0, %1, %2;" : "=r"(r) : "r"(a), "r"(b)); return r; }
__device__ __forceinline__ uint32_t hadd2_bf16(uint32_t a, uint32_t b) { uint32_t r; asm("add.rn.bf16x2 %0, %1, %2;" : "=r"(r) : "r"(a), "r"(b)); return r; }
__device__ __forceinline__ uint32_t hfma2_bf16(uint32_t a, uint32_t b, uint32_t c) { uint32_t r; asm("fma.rn.bf16x2 %0, %1, %2, %3;" : "=r"(r) : "r"(a), "r"(b), "r"(c)); return r; }
__device__ __forceinline__ void wgmma_n8(float (&d)[4], uint32_t descA, uint32_t descB, int scaleD) {
  asm volatile("{\n.reg .pred p;\n.reg .b64 da, db;\nmov.b64 da, {%4, 0x40000040};\nmov.b64 db, {%5, 0x40000040};\nsetp.ne.b32 p, %6, 0;\n"
               "wgmma.mma_async.sync.aligned.m64n8k16.f32.bf16.bf16 {%0,%1,%2,%3}, da, db, p, 1, 1, 1, 0;\n}\n"
               : "+f"(d[0]), "+f"(d[1]), "+f"(d[2]), "+f"(d[3]) : "r"(descA), "r"(descB), "r"(scaleD));
}
__device__ __forceinline__ float ex2(float x) { float r; asm("ex2.approx.ftz.f32 %0, %1;" : "=f"(r) : "f"(x)); return r; }
__device__ __forceinline__ float rcp(float x) { float r; asm("rcp.approx.ftz.f32 %0, %1;" : "=f"(r) : "f"(x)); return r; }
__device__ __forceinline__ float silu_f(float x) { return x * rcp(1.f + ex2(x * -1.4426950408889634f)); }
__device__ __forceinline__ float swiglu(float h, float hu) {
  float t; asm("tanh.approx.f32 %0, %1;" : "=f"(t) : "f"(h));
  return fmaf(hu, t, hu);
}
__device__ __forceinline__ void ldsm4(uint32_t addr, uint32_t& a, uint32_t& b, uint32_t& c, uint32_t& d) {
  asm volatile("ldmatrix.sync.aligned.m8n8.x4.shared.b16 {%0,%1,%2,%3}, [%4];" : "=r"(a), "=r"(b), "=r"(c), "=r"(d) : "r"(addr) : "memory");
}
__device__ __forceinline__ void stsm4(uint32_t addr, uint32_t a, uint32_t b, uint32_t c, uint32_t d) {
  asm volatile("stmatrix.sync.aligned.m8n8.x4.shared.b16 [%0], {%1,%2,%3,%4};" ::"r"(addr), "r"(a), "r"(b), "r"(c), "r"(d) : "memory");
}
__device__ __forceinline__ void sts128(uint32_t addr, uint32_t a, uint32_t b, uint32_t c, uint32_t d) {
  asm volatile("st.shared.v4.b32 [%0], {%1,%2,%3,%4};" ::"r"(addr), "r"(a), "r"(b), "r"(c), "r"(d) : "memory");
}
__device__ __forceinline__ void sts64(uint32_t addr, uint32_t a, uint32_t b) { asm volatile("st.shared.v2.b32 [%0], {%1,%2};" ::"r"(addr), "r"(a), "r"(b) : "memory"); }
__device__ __forceinline__ void sts32(uint32_t addr, uint32_t a) { asm volatile("st.shared.b32 [%0], %1;" ::"r"(addr), "r"(a) : "memory"); }
__device__ __forceinline__ uint4 lds128(uint32_t addr) {
  uint4 v; asm volatile("ld.shared.v4.b32 {%0,%1,%2,%3}, [%4];" : "=r"(v.x), "=r"(v.y), "=r"(v.z), "=r"(v.w) : "r"(addr) : "memory"); return v;
}
__device__ __forceinline__ uint32_t lds32(uint32_t addr) { uint32_t v; asm volatile("ld.shared.b32 %0, [%1];" : "=r"(v) : "r"(addr) : "memory"); return v; }
__device__ __forceinline__ uint32_t movm(uint32_t a) { uint32_t d; asm volatile("movmatrix.sync.aligned.m8n8.trans.b16 %0, %1;" : "=r"(d) : "r"(a)); return d; }
__device__ __forceinline__ void mma16816(float (&c)[4], uint32_t a0, uint32_t a1, uint32_t a2, uint32_t a3, uint32_t b0, uint32_t b1) {
  asm volatile("mma.sync.aligned.m16n8k16.row.col.f32.bf16.bf16.f32 {%0,%1,%2,%3},{%4,%5,%6,%7},{%8,%9},{%0,%1,%2,%3};"
               : "+f"(c[0]), "+f"(c[1]), "+f"(c[2]), "+f"(c[3]) : "r"(a0), "r"(a1), "r"(a2), "r"(a3), "r"(b0), "r"(b1));
}
__device__ __forceinline__ void mma16816z(float (&c)[4], uint32_t a0, uint32_t a1, uint32_t a2, uint32_t a3, uint32_t b0, uint32_t b1) {
  asm volatile("mma.sync.aligned.m16n8k16.row.col.f32.bf16.bf16.f32 {%0,%1,%2,%3},{%4,%5,%6,%7},{%8,%9},{%10,%10,%10,%10};"
               : "=f"(c[0]), "=f"(c[1]), "=f"(c[2]), "=f"(c[3]) : "r"(a0), "r"(a1), "r"(a2), "r"(a3), "r"(b0), "r"(b1), "f"(0.f));
}
__device__ __forceinline__ void mma1688(float (&c)[4], uint32_t a0, uint32_t a1, uint32_t b0) {
  asm volatile("mma.sync.aligned.m16n8k8.row.col.f32.bf16.bf16.f32 {%0,%1,%2,%3},{%4,%5},{%6},{%0,%1,%2,%3};"
               : "+f"(c[0]), "+f"(c[1]), "+f"(c[2]), "+f"(c[3]) : "r"(a0), "r"(a1), "r"(b0));
}
__device__ __forceinline__ float quad_max(float v) { v = fmaxf(v, __shfl_xor_sync(~0u, v, 1)); return fmaxf(v, __shfl_xor_sync(~0u, v, 2)); }
__device__ __forceinline__ float quad_sum(float v) { v += __shfl_xor_sync(~0u, v, 1); return v + __shfl_xor_sync(~0u, v, 2); }
__device__ __forceinline__ uint32_t opaque(uint32_t v) { asm volatile("" : "+r"(v)); return v; }
__device__ __forceinline__ uint32_t tid_now() { uint32_t v; asm volatile("mov.u32 %0, %%tid.x;" : "=r"(v)); return v; }
__device__ __forceinline__ void arrive_after(uint32_t bar, float v) {
  asm volatile("{\n.reg .pred p, q;\n.reg .b32 c;\nmov.b32 c, %1;\nelect.sync _|q, 0xffffffff;\n"
               "L: @q mbarrier.arrive.shared::cta.b64 _, [%0];\nsetp.eq.u32 p, c, 0x7fedcba9;\nadd.u32 c, c, 1;\nsetp.ne.u32 q, c, c;\n@p bra L;\n}"
               ::"r"(bar), "r"(__float_as_uint(v)) : "memory");
}
__device__ __forceinline__ int since(int t0) { return (int)((uint32_t)clock() - (uint32_t)t0); }
__device__ __forceinline__ void until(int t0, uint32_t t) { while ((uint32_t)since(t0) < t) {} }
__device__ __forceinline__ void in_order() { const int t = (int)clock(); while (since(t) < 0) {} }
__device__ __forceinline__ void spin(int clocks) { until((int)clock(), clocks); }

constexpr float ATT_SCALE_LOG2E = 0.17677669529663687f * 1.4426950408889634f;

constexpr int T_XA = 2600;
constexpr int P_XB = 100;
constexpr int P_ACT = 140;
constexpr int T_Q2 = 3750;
constexpr int T_Q3 = 4150;
constexpr int T_XB = 8050;
constexpr int DELAY_ST = 150;
constexpr int T_W0 = 3200;
constexpr int T_G0 = 4500;
constexpr int T_G1 = 7250;
constexpr int P_G2 = 690;
constexpr int P_G2B = 820;
constexpr int F_G2A = 700;
constexpr int F_G2B = 750;
constexpr int P_Q = 240;
constexpr int T_W = 5500;
constexpr int P_W = 1200;
constexpr int DELAY_HELP = 3000;

struct Pipe {
  const uint2* tab;
  uint32_t bars, peer_bars;
  uint2 nx;
  uint32_t prev;
  bool ready;
  bool lead;
  __device__ __forceinline__ uint2 begin(int n) {
    const uint2 e = nx;
    nx = tab[n + 1];
    if (!ready) {
      mbar_wait(bars + (e.y & 0x3ff), (e.y >> 10) & 1);
      mbar_wait(bars + ((e.y >> 16) & 0x7ff), e.y >> 31);
    }
    ready = false;
    return e;
  }
  __device__ __forceinline__ void release_now(uint32_t y) {
    asm volatile("{\n.reg .pred p, q;\n.reg .b32 c;\nmov.b32 c, %2;\nelect.sync _|q, 0xffffffff;\nsetp.ne.and.u32 q, c, 0, q;\n"
                 "L: @q mbarrier.arrive.shared::cta.b64 _, [%0];\n@q mbarrier.arrive.shared::cluster.b64 _, [%1];\n"
                 "setp.eq.u32 p, c, 1;\nadd.u32 c, c, 1;\n@p bra L;\n}"
                 ::"r"(bars + 512 + (y & 0x3ff)), "r"(peer_bars + 512 + (y & 0x3ff)), "r"(opaque(lead ? y & 0x800 : 0)) : "memory");
  }
  template <bool PAUSES = false> __device__ __forceinline__ void end(uint32_t y) {
    const bool r0 = mbar_test(bars + (nx.y & 0x3ff), (nx.y >> 10) & 1), r1 = mbar_test(bars + ((nx.y >> 16) & 0x7ff), nx.y >> 31);
    wg_wait<1>();
    release(prev);
    prev = y;
    if (PAUSES && (y & 0x1000)) { wg_wait<0>(); release(y); prev = 0; }
    ready = __all_sync(~0u, r0 && r1);
  }
  __device__ __forceinline__ void release(uint32_t y) {
    if (lead && (y & 0x800)) { if (elect_one()) { mbar_arrive(bars + 512 + (y & 0x3ff)); mbar_arrive_remote(peer_bars + 512 + (y & 0x3ff)); } }
  }
};
__device__ __forceinline__ constexpr uint32_t qa(int q) { return (q >> 1) * 256 + (q & 1) * 2; }

__device__ __forceinline__ uint32_t img_pos(uint32_t w, uint32_t lane) { return (w * 16 + (lane >> 2)) * 4 + ((lane & 3) ^ (lane >> 3)); }
__device__ __forceinline__ uint32_t img_line(uint32_t w, uint32_t lane) { return (lane >> 3) * 256 + w * 64 + (lane & 7) * 8; }

template <int MULTICAST>
__device__ __forceinline__ void tiles(uint32_t bars, const uint2* tab, uint2& nx, int n0, int n1, uint32_t dst, const char* src, uint32_t bytes,
                                      const uint32_t* cnt, uint32_t target, int pace, int head) {
  int due = 0;
#pragma unroll 1
  for (int n = n0; n < n1; n++) {
    const uint2 e = nx;
    nx = tab[n + 1];
    const uint32_t fb = bars + (e.y & 0x3ff);
    mbar_expect_tx(fb, (e.y >> 29) << 13);
    if (e.x & 0x1000000) {
      while ((int32_t)(ld_relaxed_line(cnt + ((e.x >> 25) & 31)) - target) < 0) {}
      asm volatile("fence.acquire.gpu;" ::: "memory"); fence_async_glob();
      if (!MULTICAST) due = since(head);
    }
    mbar_wait(bars + (e.x & 0x7ff), e.x >> 31);
    if (MULTICAST) bulk_g2s_mc(dst + (e.y & 0x3c000), src + (e.x & 0x3fc000), bytes, fb);
    else {
      until(due, (n - n0) * pace);
      bulk_g2s(dst + (e.y & 0x3c000), src + (e.x & 0x3fc000), bytes, fb);
    }
  }
}

template <int BOXES>
__device__ __forceinline__ void weights(uint32_t sb, uint2& nx, int& n, const CUtensorMap* m0, const CUtensorMap* m1, const CUtensorMap* m2, int c0, int c1, int c2, int dk) {
  const uint32_t bars = sb + BAR_OFF;
#pragma unroll 1
  for (bool more = true; more; n++) {
    const uint2 e = nx;
    nx = c_w[0][n + 1];
    more = !(e.y & 0x20000);
    const uint32_t fb = bars + (e.y & 0x3ff), dst = sb + W_OFF + (e.y & 0x1e000);
    const int k0 = (e.y >> 24) + dk;
    if (e.x & 0x7ff) mbar_wait(bars + (e.x & 0x7ff), (e.x >> 15) & 1);
    mbar_wait(bars + ((e.x >> 16) & 0x7ff), e.x >> 31);
    if (BOXES == 2) { tma5d_once(dst, m0, fb, c0, k0); tma5d_once(dst + 8192, m1, fb, c1, k0); }
    else { tma5d(dst, m0, fb, c0, k0); tma5d(dst + 8192, m1, fb, c1, k0); tma5d(dst + 16384, m2, fb, c2, k0); }
  }
}

__device__ __forceinline__ void mod_slice(uint32_t sb, uint32_t* dst, uint32_t tag, uint32_t w, uint32_t lane) {
  float e[4];
#pragma unroll 1
  for (int kb = 0; kb < 4; kb++) {
    mbar_wait(sb + BAR_OFF + B_SL + 8 * kb, 0);
    wg_fence();
#pragma unroll
    for (int q = 0; q < 4; q++) wgmma_n8(e, make_desc(SMEM_BASE + SL_OFF + kb * 8192, 8192) + q * 128, make_desc(SMEM_BASE + TAB_OFF + 4096 + kb * 256, 16) + q * 2, kb | q);
    wg_commit();
  }
  wg_wait<0>();
  fence_regs(e);
  if ((lane & 3) == 0) { st_relaxed(dst + w * 16 + (lane >> 2), tagf(e[0], tag)); st_relaxed(dst + w * 16 + 8 + (lane >> 2), tagf(e[2], tag)); }
  if (w == 0 && lane == 0) mbar_arrive(sb + BAR_OFF + B_SLE);
  __syncwarp();
}

__device__ __forceinline__ int mod_group(int job, int hc) { return (job >> 1) * 16 + hc * 4 + (job & 1) * 2; }

template <bool BY_SM>
__global__ void __cluster_dims__(2, 1, 1) __launch_bounds__(NTHREADS, 1) fused_kernel(const Ptrs Q, const __grid_constant__ Params P) {
  extern __shared__ __align__(1024) uint8_t smem_raw[];
  const int t0 = (int)clock();
  int cta = blockIdx.x;
  {
    uint32_t smid;
    asm volatile("mov.u32 %0, %%smid;" : "=r"(smid));
    const int tp = smid >> 1;
    const int cl = tp < 32 ? tp : (tp < 60 ? tp + 1 + (tp - 32) / 7 : (tp < 62 ? tp + 4 : (tp - 58) * 8));
    if (BY_SM) cta = cl * 2 + (cta & 1);
    cta = __shfl_sync(~0u, cta, 0);
  }
  const int grp = cta >> 4, j = cta & 15, rank = cta & 1, typ = j >> 3;
  const int wg = __shfl_sync(~0u, (int)threadIdx.x >> 7, 0);
  const int warp = __shfl_sync(~0u, (int)threadIdx.x >> 5, 0);
  const uint32_t sb = mapa(SMEM_BASE, rank), bars = sb + BAR_OFF;
  if (warp == 10 && cta < NCTA && elect_one()) {
    prefetch_tmap(&P.mWm2);
#pragma unroll
    for (int i = 0; i < 4; i++) mbar_init(bars + B_SL + 8 * i, 1);
    fence_async_smem();
    if (cta < 64) {
#pragma unroll
      for (int i = 0; i < 4; i++) {
        mbar_expect_tx(bars + B_SL + 8 * i, 8192);
        tma2d_once(sb + SL_OFF + i * 8192, &P.mWm2, bars + B_SL + 8 * i, ((cta >> 4) & 1) * D_ + (cta >> 5) * 256 + ((cta >> 2) & 3) * 64, (cta & 3) * 256 + i * 64);
      }
    }
  }
  __syncwarp();

  if (cta >= NCTA) {
    const uint32_t lane = tid_now() & 31, cf = sb + 196608, hb = cf + 16384;
    const int hc = cta - NCTA;
    if (threadIdx.x == 0) {
#pragma unroll 1
      for (int i = 0; i < 48; i++) mbar_init(hb + 8 * i, 1);
#pragma unroll 1
      for (int i = 0; i < 24; i++) mbar_init(bars + 8 * i, (i >> 1) == 6 ? 4 : 1);
    }
    const uint32_t ep = ld_relaxed(&Q.s->ep[cta * 32 + lane]) + 1;
#pragma unroll 1
    for (int kb = warp; kb < 16; kb += 12) {
      const uint32_t cv = ((const uint32_t*)Q.c)[kb * 32 + lane];
      sts32(cf + kb * 256 + (lane & 3) * 4 + (((lane >> 2) ^ ((2 * kb) & 7)) << 4), pack_bf16(silu_f(bf_lo(cv)), silu_f(bf_hi(cv))));
    }
    fence_async_smem();
    __syncthreads();
    if (wg == 2) {
      if (elect_one()) {
        spin(DELAY_HELP);
        uint32_t s = warp & 3, ph = 1;
#pragma unroll 1
        for (int n = (warp >> 1) & 1; n < 8 * 16; n += 2) {
          mbar_wait(hb + 8 * (24 + s), ph);
          mbar_expect_tx(hb + 8 * s, 8192);
          tma2d_once(sb + s * 8192, &P.mWm2, hb + 8 * s, (32 + mod_group(n >> 4, hc) + (warp & 1)) * 64, (n & 15) * 64);
          s += 4; if (s >= 24) { s -= 24; ph ^= 1; }
        }
      }
      __syncwarp();
      if (warp == 8) Q.s->ep[cta * 32 + lane] = ep;
    } else {
      uint32_t s = wg, ph = 0;
#pragma unroll 1
      for (int job = 0; job < 8; job++) {
        float e[4];
#pragma unroll 1
        for (int kb = 0; kb < 16; kb += 4) {
#pragma unroll 1
          for (int i = 0; i < 4; i++) {
            mbar_wait(hb + 8 * (s + 2 * i), ph);
            wg_fence();
#pragma unroll
            for (int q = 0; q < 4; q++)
              wgmma_n8(e, make_desc(SMEM_BASE, 8192) + (s + 2 * i) * 512 + q * 128, make_desc(SMEM_BASE + 196608, 16) + (kb + i) * 16 + q * 2, kb | i | q);
            wg_commit();
          }
          wg_wait<0>();
          if ((warp & 3) == 0 && elect_one()) {
#pragma unroll
            for (int i = 0; i < 4; i++) mbar_arrive(hb + 8 * (24 + s + 2 * i));
          }
          s += 8; if (s >= 24) { s -= 24; ph ^= 1; }
        }
        fence_regs(e);
        if ((lane & 3) == 0) {
          uint32_t* dst = Q.s->modp + (mod_group(job, hc) + wg) * 64 + (warp & 3) * 16 + (lane >> 2);
          st_relaxed(dst, tagf(e[0], tag_of(ep))); st_relaxed(dst + 8, tagf(e[2], tag_of(ep)));
          const uint32_t g = pack_bf16(2.f * __uint_as_float(tagf(e[0], tag_of(ep))), 2.f * __uint_as_float(tagf(e[2], tag_of(ep))));
          const uint32_t a = sb + PAR_OFF + ((job & 1) * 4 + wg * 2 + ((warp >> 1) & 1)) * 64 + (lane >> 3) * 16 + (warp & 1) * 8 + ((lane >> 2) & 1) * 2;
          asm volatile("st.shared.u16 [%0], %1;\nst.shared.u16 [%0 + 4], %2;" ::"r"(a), "h"((uint16_t)g), "h"((uint16_t)(g >> 16)) : "memory");
        }
        __syncwarp();
      }
    }
    __syncthreads();
    if (warp == 8) {
      if (only_one()) {
        mbar_expect_tx(bars + 64, N_HK * 32768);
#pragma unroll 1
        for (int i = 0; i < 4 * N_HK; i++) tma5d(sb + i * 8192, &P.mWd, bars + 64, hc * 256 + (i & 3) * 64, (i >> 2) * 2);
        uint32_t n = 0;
#pragma unroll 1
        for (int rb = 0; rb < 16; rb++) {
          while ((int32_t)(ld_relaxed(Q.s->cnt + (rb & 7) * 32 + (rb < 8 ? G_HK : 8 + G_ACT)) - (rb < 8 ? 4 * N_HK : 64) * ep) < 0) __nanosleep(50);
          asm volatile("fence.acquire.gpu;" ::: "memory"); fence_async_glob();
#pragma unroll 1
          for (int i = 0; i < 2 * N_HK; i++, n++) {
            mbar_wait(bars + 128 + 8 * (n & 7), ((n >> 3) & 1) ^ 1);
            mbar_expect_tx(bars + 8 * (n & 7), 8192);
            bulk_g2s(sb + 98304 + (n & 7) * 8192, Q.s->img + (size_t)((rb & 7) * N_TILES + T_ACT + (rb >> 3) * 56 + i % N_HK) * 1024 + i / N_HK * 512, 8192, bars + 8 * (n & 7));
          }
        }
      }
    } else if (warp >= 10) {
      if (only_one()) {
        const int q = warp & 1;
#pragma unroll 1
        for (int rb = 0; rb < 16; rb++) {
          mbar_wait(bars + 96 + 8 * q, rb & 1);
#pragma unroll 1
          for (int i = 0; i < 8; i++)
            asm volatile("cp.reduce.async.bulk.global.shared::cta.bulk_group.add.noftz.bf16 [%0], [%1], 4096;"
                         ::"l"(Q.s->img + (size_t)((rb & 7) * N_TILES + T_X1 + (rb >> 3) * 16 + hc * 4 + (i >> 1)) * 1024 + q * 512 + (i & 1) * 256), "r"(sb + 163840 + q * 32768 + i * 4096) : "memory");
          bulk_commit();
          bulk_wait_read();
          mbar_arrive(bars + 80 + 8 * q);
        }
        asm volatile("cp.async.bulk.wait_group 0;" ::: "memory");
        fence_async_glob(); asm volatile("fence.acq_rel.gpu;" ::: "memory");
#pragma unroll 1
        for (int i = 0; i < 8; i++) red_relaxed(Q.s->cnt + i * 32 + G_X1, 8);
      }
    } else if (wg < 2) {
      const uint32_t w = warp & 3;
      uint32_t n = wg * N_HK;
      mbar_wait(bars + 64, 0);
#pragma unroll 1
      for (int rb = 0; rb < 16; rb++) {
        float acc[128];
        mbar_wait(bars + 112 + 8 * wg, (rb & 1) ^ wg ^ 1);
#pragma unroll 1
        for (int kb = 0; kb < N_HK; kb++, n++) {
          mbar_wait(bars + 8 * (n & 7), (n >> 3) & 1);
          const uint32_t da = make_desc(SMEM_BASE + 98304, 16) + (n & 7) * 512, db = make_desc(SMEM_BASE, 8192) + kb * 2048;
          wg_fence();
#pragma unroll
          for (int q = 0; q < 4; q++) wg_n256<H64, H128>(acc, da + qa(q), db + 128 * q, q ? 1 : kb);
          wg_commit();
          wg_wait<1>();
          if (kb && w == 0 && elect_one()) mbar_arrive(bars + 128 + 8 * ((n - 1) & 7));
        }
        if (w == 0 && elect_one()) mbar_arrive(bars + 120 - 8 * wg);
        wg_wait<0>();
        if (w == 0 && elect_one()) mbar_arrive(bars + 128 + 8 * ((n - 1) & 7));
        mbar_wait(bars + 80 + 8 * wg, (rb & 1) ^ 1);
        fence_regs(acc);
        const uint32_t ln = tid_now() & 31, st = sb + 163840 + wg * 32768 + img_pos(w, ln) * 16;
        uint4 gn = lds128(sb + PAR_OFF + (ln & 3) * 16);
#pragma unroll
        for (int c = 0; c < 8; c++) {
          const uint4 g = gn;
          if (c < 7) gn = lds128(sb + PAR_OFF + (c + 1) * 64 + (ln & 3) * 16);
#pragma unroll
          for (int f = 0; f < 2; f++) {
            const float* a = &acc[16 * c + 2 * f];
            sts128(st + c * 4096 + f * 512, hmul2_bf16(g.x, pack_bf16(a[0], a[1])), hmul2_bf16(g.y, pack_bf16(a[4], a[5])),
                   hmul2_bf16(g.z, pack_bf16(a[8], a[9])), hmul2_bf16(g.w, pack_bf16(a[12], a[13])));
          }
        }
        n += N_HK;
        fence_async_smem(); __syncwarp();
        if (elect_one()) mbar_arrive(bars + 96 + 8 * wg);
      }
    }
  } else if (wg < 2) {
    asm volatile("setmaxnreg.inc.sync.aligned.u32 232;");
    const int w = warp & 3, rb = wg * 8 + grp;
    uint4* const img = Q.s->img + (size_t)grp * (N_TILES * 1024);
    uint32_t* const cnt = Q.s->cnt + grp * 32 + wg * 8;
    {
      const uint32_t tid = tid_now() & 127, lane = tid & 31;
      const uint32_t row = 8 * j + 2 * w + (lane >> 4);
      if (tid < 64) st_relaxed_b64(Q.s->stat + ((rb * 2 + rank) * 8 + (j >> 1)) * 64 + tid, 0, 0);
      uint4* dst = img + (T_H + wg * 16 + ((lane >> 3) & 1)) * 1024 + row * 8 + ((lane ^ row) & 7);
      const uint4* back = img + (T_H + wg * 16 + (lane >> 1)) * 1024 + (8 * j + 2 * w + (lane & 1)) * 8;
      const uint32_t tab = sb + TAB_OFF + (lane & 15) * 16;
      if (wg) {
        const uint32_t ep0 = ld_relaxed(&Q.s->ep[cta * 32 + lane]);
        uint32_t* mdst = Q.s->mod0 + ((cta >> 5) * 4 + (cta & 3)) * 512 + ((cta >> 2) & 7) * 64;
        const uint32_t cv = ldg32(Q.c + (cta & 3) * 256 + tid * 2);
        if (tid < 64) st_relaxed(mdst + tid, 0);
        uint4* mbox = Q.s->halo + (size_t)(grp * 16 + j) * 128 + tid;
        st_relaxed_v4(mbox, ~0u, ~0u, ~0u, ~0u); st_relaxed_v4(mbox + 128 * 128, ~0u, ~0u, ~0u, ~0u);
        const uint32_t s0 = ld_relaxed(mbox), s1 = ld_relaxed(mbox + 128 * 128);
        named_sync(0, NTHREADS);
        asm volatile("barrier.cluster.arrive.relaxed.aligned;" ::: "memory");
        in_order();
        sts32(sb + TAB_OFF + 4096 + w * 256 + (lane & 3) * 4 + (((lane >> 2) ^ (2 * w)) << 4), pack_bf16(silu_f(bf_lo(opaque(cv))), silu_f(bf_hi(cv))));
        fence_async_smem();
        if (__any_sync(~0u, (opaque(s0) & opaque(s1)) == 0)) __nanosleep(1);
        named_sync(2, 128);
        asm volatile("barrier.cluster.wait.aligned;" ::: "memory");
        const uint32_t ep = tag_of(opaque(ep0) + 1);
        uint4 xa[4];
#pragma unroll
        for (int i = 0; i < 4; i++) xa[i] = make_uint4(0, 0, 0, 0);
#pragma unroll 1
        for (int s = 0; s < 2; s++) {
          if ((cta >> 6) == s) mod_slice(sb, mdst, ep, w, lane);
          until(t0, s ? T_G1 : T_G0);
          const uint4* ms = (const uint4*)Q.s->mod0 + (2 * s + rank) * 512 + tid;
          uint4 p[4];
#pragma unroll
          for (int i = 0; i < 4; i++) p[i] = make_uint4(0, 0, 0, 0);
          uint32_t it = 0;
          do {
#pragma unroll
            for (int i = 0; i < 4; i++) if (tag_bad(p[i], ep)) p[i] = ld_relaxed_v4(ms + i * 128);
          } while (__any_sync(~0u, tag_bad(p[0], ep) | tag_bad(p[1], ep) | tag_bad(p[2], ep) | tag_bad(p[3], ep)) && ++it < POLL_MAX);
#define F4(f) ((__uint_as_float(p[0].f) + __uint_as_float(p[1].f)) + (__uint_as_float(p[2].f) + __uint_as_float(p[3].f)))
          uint32_t c0 = pack_bf16(F4(x), F4(y)), c1 = pack_bf16(F4(z), F4(w));
#undef F4
          if (w >= 2) { c0 = hadd2_bf16(c0, 0x3f803f80u); c1 = hadd2_bf16(c1, 0x3f803f80u); }
          const uint32_t ta = TAB_OFF + (tid >> 6) * 2048 + (2 * s + rank) * 512 + (tid & 63) * 8, peer = mapa(SMEM_BASE, rank ^ 1);
          asm volatile("st.async.weak.shared::cluster.mbarrier::complete_tx::bytes.v2.b32 [%0], {%2,%3}, [%1];" ::"r"(peer + ta), "r"(peer + BAR_OFF + B_ST + 8 * s), "r"(c0), "r"(c1) : "memory");
          sts64(sb + ta, c0, c1);
          if (s == 0) {
            mbar_wait(bars + B_XB, 0);
#pragma unroll
            for (int i = 0; i < 4; i++) xa[i] = lds128(sb + 4 * 16384 + (row & 7) * 2048 + 1024 + i * 256 + (lane & 15) * 16);
            landed(xa[0].x & xa[1].x & xa[2].x & xa[3].x);
          }
          __syncwarp();
          if (elect_one()) mbar_expect_tx(bars + B_ST + 8 * s, 256);
        }
        mbar_wait(bars + B_ST + 8, 0);
        const float m = __uint_as_float(lds32(sb + TAB_OFF + 6144 + tid * 8)), v = __uint_as_float(lds32(sb + TAB_OFF + 6148 + tid * 8));
#pragma unroll
        for (int i = 4; i < 8; i++) {
          const uint4 a = lds128(tab + i * 256), c = lds128(tab + 2048 + i * 256);
#define NRM(x) pack_bf16(fmaf(bf_lo(x), v, m), fmaf(bf_hi(x), v, m))
          stg128(dst - 16384 + i * 2048, hfma2_bf16(NRM(xa[i & 3].x), c.x, a.x), hfma2_bf16(NRM(xa[i & 3].y), c.y, a.y),
                 hfma2_bf16(NRM(xa[i & 3].z), c.z, a.z), hfma2_bf16(NRM(xa[i & 3].w), c.w, a.w));
#undef NRM
        }
        publish(lane >= 16 ? ld_relaxed(back - 16384) : 0, cnt - 8 + G_H1, 1);
      } else {
        named_sync(0, NTHREADS);
        asm volatile("barrier.cluster.arrive.relaxed.aligned;\nbarrier.cluster.wait.aligned;" ::: "memory");
      }
      mbar_wait(bars + B_XB + 8 * wg, 0);
      float d[64], m = 0.f, v = 0.f, m2 = 0.f, v2 = 0.f;
#pragma unroll
      for (int i = 0; i < 8; i++) {
        const uint4 t = lds128(sb + (4 + wg) * 16384 + (row & 7) * 2048 + i * 256 + (lane & 15) * 16);
        const uint32_t x[4] = {t.x, t.y, t.z, t.w};
#pragma unroll
        for (int e = 0; e < 4; e++) {
          const float d0 = bf_lo(x[e]), d1 = bf_hi(x[e]);
          d[8 * i + 2 * e] = d0; d[8 * i + 2 * e + 1] = d1;
          m += d0; m2 += d1; v = fmaf(d0, d0, v); v2 = fmaf(d1, d1, v2);
        }
      }
      m += m2; v += v2;
#pragma unroll
      for (int i = 1; i < 16; i *= 2) { m += __shfl_xor_sync(~0u, m, i); v += __shfl_xor_sync(~0u, v, i); }
      m *= 1.f / D_;
      v = rsqrtf(fmaxf(fmaf(-m, m, v * (1.f / D_)), 0.f) + 1e-5f);
      m = -m * v;
      if (!wg) {
        sts64(sb + TAB_OFF + 6144 + tid * 8, __float_as_uint(m), __float_as_uint(v));
        __syncwarp();
        if (elect_one()) mbar_arrive(bars + B_ST + 8);
      }
      mbar_wait(bars + B_ST, 0);
#pragma unroll
      for (int s = 0; s < 2; s++) {
        if (s > wg) break;
#pragma unroll
        for (int i = 4 * s; i < 4 * s + 4; i++) {
          const uint4 a = lds128(tab + i * 256), c = lds128(tab + 2048 + i * 256);
#define NRM(e) pack_bf16(fmaf(d[8 * i + 2 * e], v, m), fmaf(d[8 * i + 2 * e + 1], v, m))
          stg128(dst + i * 2048, hfma2_bf16(NRM(0), c.x, a.x), hfma2_bf16(NRM(1), c.y, a.y), hfma2_bf16(NRM(2), c.z, a.z), hfma2_bf16(NRM(3), c.w, a.w));
#undef NRM
        }
      }
      publish(wg || lane < 16 ? ld_relaxed(back) : 0, cnt + G_H0, 1);
    }

    Pipe pp;
    pp.tab = c_cons[wg];
    pp.bars = bars; pp.peer_bars = mapa(bars, rank ^ 1); pp.lead = w == 0; pp.prev = 0; pp.ready = false;
    pp.nx = pp.tab[0];
    const uint32_t dA0 = make_desc(SMEM_BASE, 16), dB0 = make_desc(SMEM_BASE + W_OFF, 8192);
    const uint32_t dAo = dA0 + rank * 512, dAp = dA0 + 512 - rank * 512;

    {
      float acc[2][96];
#pragma unroll 1
      for (int n = 0; n < 14; n++) {
        const uint2 e = pp.begin(n);
        const uint32_t da = dA0 + (e.x & 0xffff), db = dB0 + (e.x >> 16);
        wg_fence();
#pragma unroll
        for (int q = 0; q < 4; q++) {
          wg_n192<H128, H128>(acc[0], da + 2 * q, db + 128 * q, q ? 1 : n);
          wg_n192<H128, H128>(acc[1], da + 2 * q + 512, db + 128 * q, q ? 1 : n);
        }
        wg_commit();
        pp.template end<true>(e.y);
      }
      const uint2 e0 = pp.begin(14), e1 = pp.begin(15);
#pragma unroll
      for (int h = 1; h >= 0; h--) {
        wg_fence();
#pragma unroll
        for (int q = 0; q < 4; q++) wg_n192<H128, H128>(acc[h], dA0 + (e0.x & 0xffff) + 2 * q + 512 * h, dB0 + (e0.x >> 16) + 128 * q, 1);
#pragma unroll
        for (int q = 0; q < 4; q++) wg_n192<H128, H128>(acc[h], dA0 + (e1.x & 0xffff) + 2 * q + 512 * h, dB0 + (e1.x >> 16) + 128 * q, 1);
        wg_commit();
        if (h) { wg_wait<1>(); pp.release(pp.prev); }
      }
      if (pp.lead && elect_one()) mbar_arrive(bars + B_Q + 8 * wg);
      const uint2 ea = pp.begin(16);
      const uint32_t lane = tid_now() & 31, g = lane >> 2, t = lane & 3;
      const uint32_t hal = sb + (ea.x & 0xffff) * 16 + w * 2048 + lane * 16;
      uint4* mbox = Q.s->halo + (size_t)(rb * 16 + j) * 128 + lane;
      const bool first = w == 0 && grp == 0;
      uint32_t qp[2][8][2], kp[2][8][2], vp[2][8][2];
      uint4 hk[2][2], hw[2][2];
#pragma unroll
      for (int h = 1; h >= 0; h--) {
        if (h) wg_wait<1>(); else { in_order(); wg_wait<0>(); pp.release(e0.y); pp.release_now(e1.y); }
        fence_regs(acc[h]);
#pragma unroll
        for (int i = 0; i < 8; i++) {
          kp[h][i][1] = pack_bf16(acc[h][32 + 4 * i + 2], acc[h][32 + 4 * i + 3]);
          vp[h][i][1] = pack_bf16(acc[h][64 + 4 * i + 2], acc[h][64 + 4 * i + 3]);
        }
        if (h == 1 && w == 3 && grp < 7) {
#pragma unroll
          for (int d = 0; d < 2; d++) {
            st_relaxed_v4(mbox + 16 * 128 + d * 32, kp[h][4 * d][1], kp[h][4 * d + 1][1], kp[h][4 * d + 2][1], kp[h][4 * d + 3][1]);
            st_relaxed_v4(mbox + 16 * 128 + d * 32 + 64, vp[h][4 * d][1], vp[h][4 * d + 1][1], vp[h][4 * d + 2][1], vp[h][4 * d + 3][1]);
          }
        }
        if (h == 0) {
#pragma unroll
          for (int d = 0; d < 2; d++) {
            hk[0][d] = hw[0][d] = make_uint4(0, 0, 0, 0);
            if (w == 0) { hk[0][d] = ld_relaxed_v4(mbox + d * 32); hw[0][d] = ld_relaxed_v4(mbox + d * 32 + 64); }
          }
        }
#pragma unroll
        for (int i = 0; i < 8; i++) vp[h][i][1] = movm(vp[h][i][1]);
        if (h == 0 || w < 3) {
#pragma unroll
          for (int d = 0; d < 2; d++) {
            sts128(hal + 2048 + h * 8192 + d * 1024, kp[h][4 * d][1], kp[h][4 * d + 1][1], kp[h][4 * d + 2][1], kp[h][4 * d + 3][1]);
            sts128(hal + 2048 + h * 8192 + d * 1024 + 512, vp[h][4 * d][1], vp[h][4 * d + 1][1], vp[h][4 * d + 2][1], vp[h][4 * d + 3][1]);
          }
        }
        if (h == 0) {
          named_sync(1 + wg, 128);
#pragma unroll
          for (int d = 0; d < 2; d++) {
            if (w) { hk[0][d] = lds128(hal + d * 1024); hw[0][d] = lds128(hal + d * 1024 + 512); }
            hk[1][d] = lds128(hal + 8192 + d * 1024); hw[1][d] = lds128(hal + 8192 + d * 1024 + 512);
          }
        }
#pragma unroll
        for (int i = 0; i < 8; i++) {
          kp[h][i][0] = opaque(pack_bf16(acc[h][32 + 4 * i], acc[h][32 + 4 * i + 1]));
          vp[h][i][0] = movm(pack_bf16(acc[h][64 + 4 * i], acc[h][64 + 4 * i + 1]));
          qp[h][i][0] = opaque(pack_bf16(acc[h][4 * i], acc[h][4 * i + 1]));
          qp[h][i][1] = opaque(pack_bf16(acc[h][4 * i + 2], acc[h][4 * i + 3]));
        }
      }
      if (w == 0) {
        for (uint32_t it = 0; grp > 0 && it < POLL_MAX && __any_sync(~0u, empty(hk[0][0]) || empty(hk[0][1]) || empty(hw[0][0]) || empty(hw[0][1])); it++) {
#pragma unroll
          for (int d = 0; d < 2; d++) { hk[0][d] = ld_relaxed_v4(mbox + d * 32); hw[0][d] = ld_relaxed_v4(mbox + d * 32 + 64); }
        }
#pragma unroll
        for (int d = 0; d < 2; d++)
          hw[0][d] = first ? make_uint4(0, 0, 0, 0) : make_uint4(movm(hw[0][d].x), movm(hw[0][d].y), movm(hw[0][d].z), movm(hw[0][d].w));
      }
      const uint32_t hv[2][8] = {{hw[0][0].x, hw[0][0].y, hw[0][0].z, hw[0][0].w, hw[0][1].x, hw[0][1].y, hw[0][1].z, hw[0][1].w},
                                 {hw[1][0].x, hw[1][0].y, hw[1][0].z, hw[1][0].w, hw[1][1].x, hw[1][1].y, hw[1][1].z, hw[1][1].w}};
      landed(hw[0][0].x & hw[0][1].x & hw[1][0].x & hw[1][1].x);
      float s0[4][4], s1[4][4], s2[4][4];
#pragma unroll
      for (int c = 3; c >= 0; c--) {
        const int h = c >> 1, b = (c & 1) * 4;
        mma16816z(s1[c], qp[h][b][0], qp[h][b][1], qp[h][b + 1][0], qp[h][b + 1][1], kp[h][b][0], kp[h][b + 1][0]);
        mma16816z(s2[c], qp[h][b][0], qp[h][b][1], qp[h][b + 1][0], qp[h][b + 1][1], kp[h][b][1], kp[h][b + 1][1]);
        mma16816z(s0[c], qp[h][b][0], qp[h][b][1], qp[h][b + 1][0], qp[h][b + 1][1], hk[h][c & 1].x, hk[h][c & 1].y);
      }
#pragma unroll
      for (int c = 3; c >= 0; c--) {
        const int h = c >> 1, b = (c & 1) * 4 + 2;
        mma16816(s1[c], qp[h][b][0], qp[h][b][1], qp[h][b + 1][0], qp[h][b + 1][1], kp[h][b][0], kp[h][b + 1][0]);
        mma16816(s2[c], qp[h][b][0], qp[h][b][1], qp[h][b + 1][0], qp[h][b + 1][1], kp[h][b][1], kp[h][b + 1][1]);
        mma16816(s0[c], qp[h][b][0], qp[h][b][1], qp[h][b + 1][0], qp[h][b + 1][1], hk[h][c & 1].z, hk[h][c & 1].w);
      }
      arrive_after(bars + B_R + 16 * wg, s0[0][0]);
      const bool c0 = 2 * t <= g, c1 = 2 * t + 1 <= g;
      const uint32_t mcur = (c0 ? 0x0000ffffu : 0u) | (c1 ? 0xffff0000u : 0u);
      uint32_t pa[4], pb[4];
#pragma unroll
      for (int c = 3; c >= 0; c--) {
        if (c < 2 && first) { s0[c][0] = -INFINITY; s0[c][1] = -INFINITY; }
        float a0 = c0 ? s1[c][0] : s0[c][0], a1 = c1 ? s1[c][1] : s0[c][1];
        float b0 = c0 ? s2[c][2] : s1[c][2], b1 = c1 ? s2[c][3] : s1[c][3];
        const float ma = quad_max(fmaxf(a0, a1)), mb = quad_max(fmaxf(b0, b1));
        a0 = ex2((a0 - ma) * ATT_SCALE_LOG2E); a1 = ex2((a1 - ma) * ATT_SCALE_LOG2E);
        b0 = ex2((b0 - mb) * ATT_SCALE_LOG2E); b1 = ex2((b1 - mb) * ATT_SCALE_LOG2E);
        const float ia = rcp(quad_sum(a0 + a1)), ib = rcp(quad_sum(b0 + b1));
        pa[c] = opaque(pack_bf16(a0 * ia, a1 * ia)); pb[c] = opaque(pack_bf16(b0 * ib, b1 * ib));
      }
      if (pp.lead) { mbar_wait(bars + B_R + 16 * wg, 0); pp.release(ea.y); }
      float o[16][4];
#pragma unroll
      for (int i = 0; i < 16; i++) mma16816z(o[i], pa[i >> 2] & mcur, pb[i >> 2] & ~mcur, 0u, pb[i >> 2] & mcur, vp[i >> 3][i & 7][0], vp[i >> 3][i & 7][1]);
#pragma unroll
      for (int i = 0; i < 16; i++) mma1688(o[i], pa[i >> 2] & ~mcur, 0u, hv[i >> 3][i & 7]);
      arrive_after(bars + B_R + 16 * wg + 8, o[15][0]);
      uint4* tile = img + (T_ACT + wg * 56 + j) * 1024;
      uint4* dst = tile + img_pos(w, lane);
#pragma unroll
      for (int c = 0; c < 4; c++)
#pragma unroll
        for (int f = 0; f < 2; f++) {
          stg128(dst + c * 256 + f * 32, pack_bf16(o[4 * c][2 * f], o[4 * c][2 * f + 1]), pack_bf16(o[4 * c + 1][2 * f], o[4 * c + 1][2 * f + 1]),
                 pack_bf16(o[4 * c + 2][2 * f], o[4 * c + 2][2 * f + 1]), pack_bf16(o[4 * c + 3][2 * f], o[4 * c + 3][2 * f + 1]));
        }
      publish(ld_relaxed(tile + img_line(w, lane)), cnt + G_O, 1);
    }

    {
      float acc[2][64];
      uint32_t xr[32];
      {
        const uint32_t lane = tid_now() & 31;
        const uint2 e = pp.begin(17);
        const uint32_t a0 = sb + (e.x & 0xffff) * 16 + (w * 16 + (lane & 15)) * 128 + (((lane >> 4) ^ (lane & 7)) << 4);
#pragma unroll
        for (int i = 0; i < 8; i++) ldsm4((a0 ^ ((i & 3) << 5)) + (i >> 2) * 8192, xr[4 * i], xr[4 * i + 1], xr[4 * i + 2], xr[4 * i + 3]);
        landed(xr[0] & xr[4] & xr[8] & xr[12] & xr[16] & xr[20] & xr[24] & xr[28]);
        named_sync(1 + wg, 128);
        pp.release(e.y);
      }
      pp.prev = 0;
#pragma unroll 1
      for (int n = 18; n < 24; n++) {
        const uint2 e = pp.begin(n);
        const uint32_t da = e.x & 0xffff, db = dB0 + (e.x >> 16);
        wg_fence();
#pragma unroll
        for (int q = 0; q < 4; q++) {
          wg_n128<H64, H128>(acc[0], dAo + da + qa(q), db + 128 * q, q ? 1 : n - 18);
          wg_n128<H64, H128>(acc[1], dAp + da + qa(q), db + 128 * q, q ? 1 : n - 18);
        }
        wg_commit();
        pp.template end<true>(e.y);
      }
      const uint2 e0 = pp.begin(24);
      const uint2 e1 = pp.begin(25);
#pragma unroll
      for (int h = 1; h >= 0; h--) {
        wg_fence();
#pragma unroll
        for (int q = 0; q < 4; q++) wg_n128<H64, H128>(acc[h], (h ? dAp : dAo) + (e0.x & 0xffff) + qa(q), dB0 + (e0.x >> 16) + 128 * q, 1);
#pragma unroll
        for (int q = 0; q < 4; q++) wg_n128<H64, H128>(acc[h], (h ? dAp : dAo) + (e1.x & 0xffff) + qa(q), dB0 + (e1.x >> 16) + 128 * q, 1);
        wg_commit();
      }
      const uint32_t tid = tid_now() & 127, lane = tid & 31;
      const uint2 ea = pp.begin(26);
      const uint32_t px = (ea.x & 0xffff) * 16 + tid * 16;
      wg_wait<1>();
      pp.release_now(pp.prev);
      fence_regs(acc[1]);
#pragma unroll
      for (int i = 0; i < 8; i++)
        st_async(pp.peer_bars - BAR_OFF + px + i * 2048, pp.peer_bars + (pp.nx.y & 0x3ff), pack_bf16(acc[1][8 * i], acc[1][8 * i + 1]), pack_bf16(acc[1][8 * i + 2], acc[1][8 * i + 3]),
                 pack_bf16(acc[1][8 * i + 4], acc[1][8 * i + 5]), pack_bf16(acc[1][8 * i + 6], acc[1][8 * i + 7]));
      wg_wait<0>();
      pp.release(e0.y); pp.release(e1.y); pp.release_now(ea.y);
      fence_regs(acc[0]);
      const uint32_t ep = tag_of(lds32(bars + ROLE_OFF + 4));
      mbar_wait(bars + B_PAR, 0);
      uint32_t pr[3][16];
#pragma unroll
      for (int i = 0; i < 4; i++) {
        const uint4 x = lds128(sb + PAR_OFF + (i >> 2) * 256 + (lane & 3) * 64 + (i & 3) * 16);
        pr[i >> 2][(i & 3) * 4] = x.x; pr[i >> 2][(i & 3) * 4 + 1] = x.y; pr[i >> 2][(i & 3) * 4 + 2] = x.z; pr[i >> 2][(i & 3) * 4 + 3] = x.w;
      }
      const uint2 eb = pp.begin(27);
      float sm[2] = {0.f, 0.f}, sq[2] = {0.f, 0.f};
#pragma unroll
      for (int c = 0; c < 8; c++) {
        const uint4 z = lds128(sb + px + c * 2048);
        const uint32_t zz[4] = {z.x, z.y, z.z, z.w};
#pragma unroll
        for (int b = 0; b < 4; b++) {
          const int i = 4 * c + b;
          xr[i] = hfma2_bf16(pr[0][i >> 1], hadd2_bf16(pack_bf16(acc[0][2 * i], acc[0][2 * i + 1]), zz[b]), xr[i]);
          const float d0 = bf_lo(xr[i]), d1 = bf_hi(xr[i]);
          acc[0][2 * i] = d0; acc[0][2 * i + 1] = d1;
          sm[i & 1] += d0 + d1;
          sq[i & 1] = fmaf(d0, d0, fmaf(d1, d1, sq[i & 1]));
        }
      }
      {
        const bool b0 = lane & 1;
        sm[0] = (b0 ? sm[1] : sm[0]) + __shfl_xor_sync(~0u, b0 ? sm[0] : sm[1], 1);
        sq[0] = (b0 ? sq[1] : sq[0]) + __shfl_xor_sync(~0u, b0 ? sq[0] : sq[1], 1);
        sm[0] += __shfl_xor_sync(~0u, sm[0], 2);
        sq[0] += __shfl_xor_sync(~0u, sq[0], 2);
      }
      uint2* ss = Q.s->stat + (rb * 2 + rank) * 512 + w * 16 + (lane >> 2) * 2 + (lane & 1);
      if (!(lane & 2)) st_relaxed_b64(ss + (j >> 1) * 64, tagf(sm[0], ep), tagf(sq[0], ep));
      named_sync(1 + wg, 128);
      pp.release(eb.y);
      mbar_wait(bars + B_PAR + 8, 0);
#pragma unroll
      for (int i = 4; i < 12; i++) {
        const uint4 x = lds128(sb + PAR_OFF + (i >> 2) * 256 + (lane & 3) * 64 + (i & 3) * 16);
        pr[i >> 2][(i & 3) * 4] = x.x; pr[i >> 2][(i & 3) * 4 + 1] = x.y; pr[i >> 2][(i & 3) * 4 + 2] = x.z; pr[i >> 2][(i & 3) * 4 + 3] = x.w;
      }
      {
        ss += (lane & 2) * 128;
        uint2 p[4];
#pragma unroll
        for (int i = 0; i < 4; i++) p[i] = make_uint2(0, 0);
        spin(DELAY_ST);
        uint32_t it = 0, bad;
        do {
          bad = 0;
#pragma unroll
          for (int i = 0; i < 4; i++) if (((p[i].x ^ ep) | (p[i].y ^ ep)) & 3u) p[i] = ld_relaxed_b64(ss + i * 64);
#pragma unroll
          for (int i = 0; i < 4; i++) bad |= (p[i].x ^ ep) | (p[i].y ^ ep);
        } while (__any_sync(~0u, bad & 3u) && ++it < POLL_MAX);
        float m = (__uint_as_float(p[0].x) + __uint_as_float(p[1].x)) + (__uint_as_float(p[2].x) + __uint_as_float(p[3].x));
        float v = (__uint_as_float(p[0].y) + __uint_as_float(p[1].y)) + (__uint_as_float(p[2].y) + __uint_as_float(p[3].y));
        m += __shfl_xor_sync(~0u, m, 2); v += __shfl_xor_sync(~0u, v, 2);
        m *= 1.f / D_;
        v = rsqrtf(fmaxf(fmaf(-m, m, v * (1.f / D_)), 0.f) + 1e-5f);
        m = -m * v;
#pragma unroll
        for (int r = 0; r < 2; r++) { sm[r] = __shfl_sync(~0u, m, r, 2); sq[r] = __shfl_sync(~0u, v, r, 2); }
      }
      uint4* tile = img + (T_H + wg * 16 + (j & 14)) * 1024 + rank * 512;
      uint4* dst = tile + img_pos(w, lane);
#pragma unroll
      for (int c = 0; c < 4; c++)
#pragma unroll
        for (int f = 0; f < 2; f++) {
          uint32_t y[4];
#pragma unroll
          for (int b = 0; b < 4; b++) {
            const int i = c * 4 + b;
            y[b] = hfma2_bf16(pack_bf16(fmaf(acc[0][4 * i + 2 * f], sq[f], sm[f]), fmaf(acc[0][4 * i + 2 * f + 1], sq[f], sm[f])), pr[2][i], pr[1][i]);
          }
          stg128(dst + (c >> 1) * 1024 + (c & 1) * 256 + f * 32, y[0], y[1], y[2], y[3]);
        }
      publish(ld_relaxed(tile + img_line(w, lane) + (lane >> 4) * 512), cnt + G_H2, 1);
#pragma unroll
      for (int c = 0; c < 4; c++)
#pragma unroll
        for (int f = 0; f < 2; f++) {
          stg128(dst + (T_X1 - T_H + (c >> 1)) * 1024 + (c & 1) * 256 + f * 32, xr[8 * c + f], xr[8 * c + 2 + f], xr[8 * c + 4 + f], xr[8 * c + 6 + f]);
        }
    }

    float acc[2][64], ax[32];
    uint32_t px_y;
    {
      float a3[2][96];
      pp.prev = 0;
#pragma unroll 1
      for (int n = 28; n < 44; n++) {
        const uint2 e = pp.begin(n);
        const uint32_t da = e.x & 0xffff, db = dB0 + (e.x >> 16);
        wg_fence();
#pragma unroll
        for (int q = 0; q < 4; q++) {
          wg_n192<H64, H128>(a3[0], dAo + da + qa(q), db + 128 * q, q ? 1 : n - 28);
          wg_n192<H64, H128>(a3[1], dAp + da + qa(q), db + 128 * q, q ? 1 : n - 28);
        }
        wg_commit();
        pp.end(e.y);
      }
      px_y = pp.nx.y;
      pp.nx = pp.tab[45]; pp.ready = false;
      mbar_wait(bars + ((px_y >> 16) & 0x7ff), px_y >> 31);
      wg_wait<0>();
      pp.release_now(pp.prev);
      fence_regs(a3[0]); fence_regs(a3[1]);
      pp.prev = 0;
#pragma unroll
      for (int i = 0; i < 4; i++)
        st_async(pp.peer_bars - 8192 + (tid_now() & 127) * 16 + i * 2048, pp.peer_bars + (px_y & 0x3ff), pack_bf16(a3[1][64 + 8 * i], a3[1][65 + 8 * i]),
                 pack_bf16(a3[1][66 + 8 * i], a3[1][67 + 8 * i]), pack_bf16(a3[1][68 + 8 * i], a3[1][69 + 8 * i]), pack_bf16(a3[1][70 + 8 * i], a3[1][71 + 8 * i]));
#pragma unroll
      for (int i = 0; i < 64; i++) { acc[0][i] = a3[0][i]; acc[1][i] = a3[1][i]; }
#pragma unroll
      for (int i = 0; i < 32; i++) ax[i] = a3[0][64 + i];
    }
    uint32_t seen, seen2;
#pragma unroll 1
    for (int T = 0;; T++) {
      wg_wait<0>();
      pp.release_now(pp.prev);
      fence_regs(acc[0]); fence_regs(acc[1]);
      pp.prev = 0;
      {
        const uint32_t lane = tid_now() & 31;
        uint4* tile = img + (T_ACT + wg * 56 + (T ? 8 + 16 * T : 0) + j) * 1024;
        uint4* tx = img + (T_ACT + wg * 56 + 16 + (j >> 1)) * 1024 + rank * 512;
        const int ts = (int)clock();
#pragma unroll
        for (int c = 0; c < 4; c++)
#pragma unroll
          for (int f = 0; f < 2; f++) {
            uint32_t y[4];
#pragma unroll
            for (int b = 0; b < 4; b++) {
              const int i = ((c & 1) * 4 + b) * 4 + 2 * f;
              y[b] = pack_bf16(swiglu(acc[c >> 1][i], acc[c >> 1][i] * acc[c >> 1][32 + i]), swiglu(acc[c >> 1][i + 1], acc[c >> 1][i + 1] * acc[c >> 1][33 + i]));
            }
            stg128(tile + img_pos(w, lane) + ((c >> 1) ^ rank) * 512 + (c & 1) * 256 + f * 32, y[0], y[1], y[2], y[3]);
            if (c + f < 4) until(ts, (2 * c + f + 1) * P_ACT);
            fence_regs(acc[0]); fence_regs(acc[1]);
          }
        if (T == 0) {
          if (wg == 0 && j < N_HK) publish(ld_relaxed(tile + img_line(w, lane)), cnt + G_HK, 1);
          mbar_wait(bars + (px_y & 0x3ff), 1);
          uint32_t z[16];
#pragma unroll
          for (int i = 0; i < 4; i++) { const uint4 x = lds128(bars - 8192 + (tid_now() & 127) * 16 + i * 2048); z[4 * i] = x.x; z[4 * i + 1] = x.y; z[4 * i + 2] = x.z; z[4 * i + 3] = x.w; }
          landed(z[0] & z[4] & z[8] & z[12]);
          named_sync(1 + wg, 128);
          pp.release(px_y);
#pragma unroll
          for (int c = 0; c < 2; c++)
#pragma unroll
            for (int f = 0; f < 2; f++) {
              uint32_t y[4];
#pragma unroll
              for (int b = 0; b < 4; b++) {
                const int i = (c * 4 + b) * 2 + f;
                const float o0 = bf_lo(z[i]), o1 = bf_hi(z[i]);
                y[b] = pack_bf16(swiglu(rank ? o0 : ax[2 * i], o0 * ax[2 * i]), swiglu(rank ? o1 : ax[2 * i + 1], o1 * ax[2 * i + 1]));
              }
              stg128(tx + img_pos(w, lane) + c * 256 + f * 32, y[0], y[1], y[2], y[3]);
            }
        }
        seen = ld_relaxed(tile + img_line(w, lane));
        seen2 = ld_relaxed(tx + img_line(w, lane & 15));
      }
      if (T == 2) break;
      const int n0 = 45 + 16 * T, n1 = n0 + 16;
#pragma unroll 1
      for (int n = n0; n < n1; n++) {
        const uint2 e = pp.begin(n);
        const uint32_t da = e.x & 0xffff, db = dB0 + (e.x >> 16);
        wg_fence();
#pragma unroll
        for (int q = 0; q < 4; q++) {
          wg_n128<H64, H128>(acc[0], dAo + da + qa(q), db + 128 * q, q ? 1 : n - n0);
          wg_n128<H64, H128>(acc[1], dAp + da + qa(q), db + 128 * q, q ? 1 : n - n0);
        }
        wg_commit();
        if (n == n0 + 1) publish(opaque(seen) & opaque(seen2), cnt + G_ACT + T, 1);
        pp.end(e.y);
      }
    }
    {
      uint32_t gp[16];
#pragma unroll
      for (int ph = 0; ph < 2; ph++) {
#pragma unroll 1
        for (int n = ph ? 90 : 77; n < (ph ? N_END - N_PEEL : 90); n++) {
          const uint2 e = pp.begin(n);
          const uint32_t da = dA0 + wg * 512 + (e.x & 0xffff), db = dB0 + (e.x >> 16);
          wg_fence();
#pragma unroll
          for (int q = 0; q < 4; q++) wg_n128<H64, H128>(acc[0], da + qa(q), db + 128 * q, q || ph ? 1 : n - 77);
          wg_commit();
          pp.end(e.y);
        }
        if (ph == 0) {
          publish(opaque(seen) & opaque(seen2), cnt + G_ACT + 2, 1);
          mbar_wait(bars + B_GB, 0);
#pragma unroll
          for (int i = 0; i < 4; i++) {
            const uint4 x = lds128(sb + PAR_OFF + 768 + (tid_now() & 3) * 64 + i * 16);
            gp[4 * i] = x.x; gp[4 * i + 1] = x.y; gp[4 * i + 2] = x.z; gp[4 * i + 3] = x.w;
          }
        }
      }
#pragma unroll
      for (int n = N_END - N_PEEL; n < N_END; n++) {
        const uint2 e = pp.begin(n);
        const uint32_t da = dA0 + wg * 512 + (e.x & 0xffff), db = dB0 + (e.x >> 16);
        wg_fence();
#pragma unroll
        for (int q = 0; q < 4; q++) wg_n128<H64, H128>(acc[0], da + qa(q), db + 128 * q, 1);
        wg_commit();
        if (n == N_END - N_PEEL) { wg_wait<1>(); pp.release(pp.prev); pp.prev = 0; }
      }
      const uint32_t lane = tid_now() & 31;
      uint32_t xp[32];
      {
        const uint2 e0 = pp.begin(N_END), e1 = pp.begin(N_END + 1);
#pragma unroll
        for (int i = 0; i < 8; i++) {
          const uint4 r = lds128(sb + (((i & 4 ? e1.x : e0.x) & 0xffff) + wg * 512 + img_pos(w, lane) + ((i >> 1) & 1) * 256 + (i & 1) * 32) * 16);
          xp[(i >> 1) * 8 + (i & 1)] = r.x; xp[(i >> 1) * 8 + 2 + (i & 1)] = r.y; xp[(i >> 1) * 8 + 4 + (i & 1)] = r.z; xp[(i >> 1) * 8 + 6 + (i & 1)] = r.w;
        }
      }
      const uint32_t st = sb + ((w & 2) ? pp.nx.x >> 16 : pp.nx.x & 0xffff) * 16 + wg * 8192 + (w & 1) * 4096;
      const uint32_t a0 = opaque(st + (lane & 15) * 128 + (((lane >> 4) ^ (lane & 7)) << 4));
      if (pp.lead && elect_one()) mbar_arrive(bars + B_END);
      wg_wait<0>();
      pp.release_now(pp.prev);
      fence_regs(acc[0]);
#pragma unroll
      for (int c = 0; c < 4; c++) {
        uint32_t y[2][4];
#pragma unroll
        for (int f = 0; f < 2; f++)
#pragma unroll
          for (int b = 0; b < 4; b++) {
            const int i = 16 * c + 4 * b + 2 * f;
            y[f][b] = hfma2_bf16(gp[4 * c + b], pack_bf16(acc[0][i], acc[0][i + 1]), xp[8 * c + 2 * b + f]);
          }
        stsm4((a0 ^ ((c & 1) << 6)) + (c >> 1) * 2048, y[0][0], y[1][0], y[0][1], y[1][1]);
        stsm4((a0 ^ ((c & 1) << 6) ^ 32) + (c >> 1) * 2048, y[0][2], y[1][2], y[0][3], y[1][3]);
        if (c == 1) {
          fence_async_smem(); __syncwarp();
          if (elect_one()) {
            tma2d_st(&P.mOut, st, typ * D_ + (j & 7) * 128, grp * 128 + wg * 64 + w * 16);
            bulk_commit();
          }
        }
      }
      {
        __syncwarp();
        const uint32_t ln = tid_now() & 31;
        uint4* op = (uint4*)(Q.out + (size_t)(grp * 256 + 2 * (wg * 64 + w * 16 + (ln >> 3)) + typ) * D_ + (j & 7) * 128 + 64) + (ln & 7);
        uint4 r[4];
#pragma unroll
        for (int k = 0; k < 4; k++) r[k] = lds128(st + 2048 + ((ln >> 3) + 4 * k) * 128 + (((ln & 7) ^ (((ln >> 3) + 4 * k) & 7)) << 4));
#pragma unroll
        for (int k = 0; k < 4; k++) stg128(op + k * D_, r[k].x, r[k].y, r[k].z, r[k].w);
        if (elect_one()) bulk_wait_read();
      }
    }
  } else {
    asm volatile("setmaxnreg.dec.sync.aligned.u32 40;");
    const uint32_t lane = tid_now() & 31;
    if (elect_one()) {
      if (warp == 10) {
        prefetch_tmap(&P.mWqkv);
#pragma unroll
        for (int i = 0; i < 12; i++) mbar_init(bars + 1024 + 8 * i, i < 4 ? 4 : 1);
        mbar_init(bars + B_ST, 4); mbar_init(bars + B_ST + 8, 8); mbar_init(bars + B_XB, 1); mbar_init(bars + B_XB + 8, 1); mbar_init(bars + B_END, 2);
        sts32(bars + ROLE_OFF, cta >> 1);
      } else if (warp == 11) {
#pragma unroll 1
        for (int u = 0; u < 2; u++) {
#pragma unroll
          for (int i = 0; i < 20; i++) mbar_init(bars + u * 512 + 352 + 8 * i, 1 + u);
        }
      } else {
#pragma unroll 22
        for (int i = 0; i < 44; i++) mbar_init(bars + (warp & 1) * 512 + 8 * i, 1 + (warp & 1));
      }
      asm volatile("fence.mbarrier_init.release.cluster;" ::: "memory");
    }
    named_sync(0, NTHREADS);
    asm volatile("barrier.cluster.arrive.relaxed.aligned;" ::: "memory");
    asm volatile("barrier.cluster.wait.aligned;" ::: "memory");
    const uint32_t ep0 = ld_relaxed(&Q.s->ep[cta * 32 + lane]);
    if (!(warp & 1)) {
      if (only_one()) {
        const int q = (warp >> 1) & 1;
        const uint2* tab = c_act[q];
        const char* src = (const char*)(Q.s->img + (size_t)grp * (N_TILES * 1024) + rank * 512);
        const uint32_t sa = sb + rank * 8192;
        if (q) {
          if (cta >= 64) {
#pragma unroll 1
            for (int i = 0; i < 4; i++) {
              until(t0, (cta >= 96 ? T_Q3 : T_Q2) + i * P_Q);
              mbar_expect_tx(bars + B_SL + 8 * i, 8192);
              tma2d_once(sb + SL_OFF + i * 8192, &P.mWm2, bars + B_SL + 8 * i, ((cta >> 4) & 1) * D_ + (cta >> 5) * 256 + ((cta >> 2) & 3) * 64, (cta & 3) * 256 + i * 64);
            }
          }
        }
        mbar_expect_tx(bars + B_XB + 8 * q, 16384);
#pragma unroll 1
        for (int i = 0; i < 8; i++) {
          until(t0, q ? T_XB + i * P_XB : T_XA);
          bulk_g2s(sb + (4 + q) * 16384 + i * 2048, Q.x + (size_t)(cta * 16 + 2 * i + q) * D_, 2048, bars + B_XB + 8 * q);
        }
        const uint32_t target = (opaque(ep0) + 1) * 64;
        const uint32_t* cnt = Q.s->cnt + grp * 32;
        const char* x1 = src + (T_X1 + typ * 16 + (j & 7) * 2) * 16384 + (q - rank) * 8192;
        uint2 nx = tab[0];
#pragma unroll 1
        for (int ph = 0; ph < 4; ph++) {
          const bool half = ph == 3;
          tiles<1>(bars, tab, nx, half ? 77 : (ph ? 11 + 17 * ph : 0), half ? N_END : (ph ? 11 + 33 * ph : 16), half ? sb + q * 8192 + rank * 4096 : sa,
                   half ? src + typ * 56 * 16384 + q * 8192 - rank * 4096 : src, half ? 4096 : 8192, half ? cnt + typ * 8 : cnt, target, 0, 0);
          if (ph == 1) { mbar_expect_tx(bars + (nx.y & 0x3ff), 8192); nx = tab[45]; }
          if (ph) continue;
#pragma unroll 1
          for (int n = 16; n < 28; n++) {
            const uint2 e = nx;
            nx = tab[n + 1];
            const uint32_t fb = bars + (e.y & 0x3ff);
            mbar_wait(bars + (e.x & 0x7ff), e.x >> 31);
            mbar_expect_tx(fb, (e.y >> 29) << 13);
            if (n == 17) {
              tma2d(sb + (e.y & 0x3c000), &P.mX, fb, q * D_ + (j & 14) * 64, grp * 128 + rank * 64);
              tma2d(sb + (e.y & 0x3c000) + 8192, &P.mX, fb, q * D_ + (j | 1) * 64, grp * 128 + rank * 64);
              tiles<0>(bars, tab, nx, 18, 26, sb, src + rank * 8192, 16384, cnt, target, q ? P_G2B : P_G2, q ? F_G2B : F_G2A);
              n = 25;
            }
          }
        }
        while ((int32_t)(ld_relaxed_line(cnt + G_X1) - target) < 0) {}
        asm volatile("fence.acquire.gpu;" ::: "memory"); fence_async_glob();
#pragma unroll 1
        for (int n = 0; n < 2; n++) {
          const uint2 e = tab[N_END + n];
          const uint32_t fb = bars + (e.y & 0x3ff);
          mbar_expect_tx(fb, 8192);
          mbar_wait(bars + (e.x & 0x7ff), e.x >> 31);
          bulk_g2s(sb + q * 8192 + (e.y & 0x3c000), x1 + n * 16384, 8192, fb);
        }
      }
    } else if (warp == 9) {
      if (only_one()) {
        uint2 nx = c_w[0][0];
#pragma unroll 1
        for (int n = 0; n < N_W;) {
          if (n < 5) until(t0, n ? T_W + (n - 1) * P_W : T_W0);
          if (n == 2) mbar_wait(bars + B_SLE, 0);
          if (n == 5) { prefetch_tmap(&P.mWo); prefetch_tmap(&P.mWg); prefetch_tmap(&P.mWu); prefetch_tmap(&P.mWd); prefetch_tmap(&P.mX); }
          const int u = (nx.y >> 10) & 7;
          if (u < 2) {
            weights<3>(sb, nx, n, u ? &P.mWg : &P.mWqkv, u ? &P.mWu : &P.mWqkv, u ? &P.mWg + rank : &P.mWqkv,
                       j * 64, (u ? 0 : D_) + j * 64, u ? 1024 + (j >> 1) * 64 : 2 * D_ + j * 64, 0);
          } else {
            const bool ffn = u == 3 || u == 4;
            const int c0 = ffn ? u * 1024 - 1536 + j * 64 : (u == 2 ? j >> 1 : j & 7) * 128;
            const CUtensorMap* m0 = ffn ? &P.mWg : (u == 2 ? &P.mWo : &P.mWd);
            weights<2>(sb, nx, n, m0, m0 + ffn, nullptr, c0, ffn ? c0 : c0 + 64, 0, u == 2 ? rank * 2 : 0);
          }
        }
        prefetch_tmap(&P.mOut);
      }
    } else {
      {
        const uint32_t i = opaque((grp * 2 + rank) * 8), k = i < N_W - 128 ? i + 128 : 128;
        if ((c_cons[0][i].x & c_cons[1][i].x & c_act[0][i].y & c_act[1][i].y & c_w[0][i].y & c_w[0][k].y) == 0xffffffffu) __trap();
      }
      const uint32_t ep = opaque(ep0) + 1;
      if (lane == 0) {
        sts32(bars + ROLE_OFF + 4, ep);
        uint32_t pr; asm volatile("ld.shared::cluster.u32 %0, [%1];" : "=r"(pr) : "r"(mapa(bars + ROLE_OFF, rank ^ 1)) : "memory");
        if (pr != (uint32_t)(cta >> 1) || sb != smem_u32(smem_raw)) { __trap(); }
      }
      const uint32_t tag = tag_of(ep);
#pragma unroll 1
      for (int i = 0; i < 8; i++) {
        const uint2* src = (const uint2*)(Q.s->modp + (i >> 1) * 1024 + (i < 6 ? j >> 1 : j & 7) * 128 + (i & 1) * 64) + lane;
        uint2 a; uint32_t it = 0;
        do { if (it) __nanosleep(200); a = ld_relaxed_b64(src); guard(++it); } while (__any_sync(~0u, ((a.x ^ tag) | (a.y ^ tag)) & 3u));
        uint32_t p = pack_bf16(__uint_as_float(a.x), __uint_as_float(a.y));
        if ((i >> 1) == 2) p = pack_bf16(1.f + bf_lo(p), 1.f + bf_hi(p));
        const float sc = i < 2 ? 1.f : (i < 6 ? 0.5f : 2.f);
        p = pack_bf16(sc * bf_lo(p), sc * bf_hi(p));
        sts32(sb + PAR_OFF + (i >> 1) * 256 + (lane & 3) * 64 + (i & 1) * 32 + (lane >> 2) * 4, p);
        __syncwarp();
        if ((i == 1 || i == 5 || i == 7) && elect_one()) { mbar_arrive(bars + (i == 7 ? B_GB : B_PAR + (i & 4) * 2)); }
      }
      mbar_wait_bounded(bars + B_R, 0);
      Q.s->ep[cta * 32 + lane] = ep;
      mbar_wait_bounded(bars + B_END, 0);
    }
  }
}

typedef CUresult (*PFN_encodeTiled)(CUtensorMap*, CUtensorMapDataType, cuuint32_t, void*, const cuuint64_t*, const cuuint64_t*,
                                    const cuuint32_t*, const cuuint32_t*, CUtensorMapInterleave, CUtensorMapSwizzle,
                                    CUtensorMapL2promotion, CUtensorMapFloatOOBfill);

void make_map(PFN_encodeTiled enc, CUtensorMap* m, const void* ptr, uint64_t inner, uint64_t outer, uint32_t box_outer, int promo = CU_TENSOR_MAP_L2_PROMOTION_L2_256B) {
  cuuint64_t dims[2] = {inner, outer};
  cuuint64_t strides[1] = {inner * 2};
  cuuint32_t box[2] = {64, box_outer};
  cuuint32_t es[2] = {1, 1};
  enc(m, CU_TENSOR_MAP_DATA_TYPE_BFLOAT16, 2, const_cast<void*>(ptr), dims, strides, box, es, CU_TENSOR_MAP_INTERLEAVE_NONE,
      CU_TENSOR_MAP_SWIZZLE_128B, (CUtensorMapL2promotion)promo, CU_TENSOR_MAP_FLOAT_OOB_FILL_NONE);
}
void make_wmap(PFN_encodeTiled enc, CUtensorMap* m, const void* ptr, uint64_t cols, uint64_t rows, bool permuted) {
  cuuint64_t dims[5] = {cols, 2, 4, 4, rows / 32};
  cuuint64_t strides[4] = {cols * 2, cols * 2 * (permuted ? 8 : 2), cols * 2 * (permuted ? 2 : 8), cols * 2 * 32};
  cuuint32_t box[5] = {64, 2, 4, 4, 2};
  cuuint32_t es[5] = {1, 1, 1, 1, 1};
  enc(m, CU_TENSOR_MAP_DATA_TYPE_BFLOAT16, 5, const_cast<void*>(ptr), dims, strides, box, es, CU_TENSOR_MAP_INTERLEAVE_NONE,
      CU_TENSOR_MAP_SWIZZLE_128B, CU_TENSOR_MAP_L2_PROMOTION_L2_128B, CU_TENSOR_MAP_FLOAT_OOB_FILL_NONE);
}

}

extern "C" void kernel_launch(void* const* d_in, const int* in_sizes, int n_in, void* d_out, int out_size) {
  (void)in_sizes; (void)n_in; (void)out_size;
  static PFN_encodeTiled enc = nullptr;
  static void* scratch = nullptr;
  static int sms = 0;
  if (!enc) {
    int dev = 0;
    cudaGetDevice(&dev);
    cudaDeviceGetAttribute(&sms, cudaDevAttrMultiProcessorCount, dev);
    cudaGetSymbolAddress(&scratch, g_s);
    void* fn = nullptr;
    cudaDriverEntryPointQueryResult q;
    cudaGetDriverEntryPoint("cuTensorMapEncodeTiled", &fn, cudaEnableDefault, &q);
    enc = (PFN_encodeTiled)fn;
    cudaFuncSetAttribute(fused_kernel<true>, cudaFuncAttributeMaxDynamicSharedMemorySize, SMEM_BYTES);
    cudaFuncSetAttribute(fused_kernel<false>, cudaFuncAttributeMaxDynamicSharedMemorySize, SMEM_BYTES);
  }
  Params P;
  make_wmap(enc, &P.mWqkv, d_in[1], 3 * D_, D_, false);
  make_wmap(enc, &P.mWo, d_in[2], D_, D_, true);
  make_wmap(enc, &P.mWg, d_in[4], F_, D_, true);
  make_wmap(enc, &P.mWu, d_in[5], F_, D_, true);
  make_wmap(enc, &P.mWd, d_in[6], D_, F_, true);
  make_map(enc, &P.mOut, d_out, 2 * D_, S_ / 2, 16);
  make_map(enc, &P.mX, d_in[0], 2 * D_, S_ / 2, 64, CU_TENSOR_MAP_L2_PROMOTION_L2_128B);
  make_map(enc, &P.mWm2, d_in[8], 6 * D_, D_, 64, CU_TENSOR_MAP_L2_PROMOTION_L2_128B);
  Ptrs Q;
  Q.s = (Scratch*)scratch;
  Q.x = (const __nv_bfloat16*)d_in[0];
  Q.c = (const __nv_bfloat16*)d_in[7];
  Q.out = (__nv_bfloat16*)d_out;
  if (sms == NCTA + 4) fused_kernel<true><<<NCTA + 4, NTHREADS, SMEM_BYTES, cudaStreamPerThread>>>(Q, P);
  else fused_kernel<false><<<NCTA + 4, NTHREADS, SMEM_BYTES, cudaStreamPerThread>>>(Q, P);
}
```
